```python
import torch

def _softmax(x, axis=-1):
    return torch.softmax(x, dim=axis)
def _gelu(x):
    return torch.nn.functional.gelu(x, approximate="tanh")
def _silu(x):
    return torch.nn.functional.silu(x)
def _sigmoid(x):
    return torch.sigmoid(x)
def _layernorm(x, axis=-1, eps=1e-5):
    m = x.mean(dim=axis, keepdim=True)
    v = x.var(dim=axis, keepdim=True, unbiased=False)
    return (x - m) / torch.sqrt(v + eps)
def _scatter_add(tgt, idx, src, axis=0):
    return tgt.clone().index_add_(axis, idx, src)
def _segment_sum(src, seg, n):
    out = torch.zeros((n,) + src.shape[1:], dtype=src.dtype)
    return out.index_add_(0, seg, src)
def _pad(x, pw):
    flat = tuple(v for pair in reversed(pw) for v in pair)
    return torch.nn.functional.pad(x, flat)

kernel_name = 'gated_mix__compressed_kv_cla__mixer_token_mlp__decode'

def setup_inputs():

    _w = (lambda a: (lambda t: t.to(torch.bfloat16) if t.is_floating_point() else t)(torch.as_tensor(a)))
    def _A_setup():
        B, H, Sq, Sk, D, M = 4, 32, 1, 4096, 128, 576
        Dc = 4 * D
        return {
            "x": _w((lambda *s: torch.randn(*s, dtype=torch.bfloat16) * 0.05)(B, Sq, M)),
            "c_kv": _w((lambda *s: torch.randn(*s, dtype=torch.bfloat16) * 0.4)(B, Sk, Dc)),
            "w_q": _w((lambda *s: torch.randn(*s, dtype=torch.bfloat16) * 3.2)(M, H, D) * (M ** -0.5)),
            "w_uk": _w((lambda *s: torch.randn(*s, dtype=torch.bfloat16) * 3.2)(Dc, H, D) * (Dc ** -0.5)),
            "w_uv": _w((lambda *s: torch.randn(*s, dtype=torch.bfloat16) * 0.4)(Dc, H, D) * (Dc ** -0.5)),
            "w_o": _w((lambda *s: torch.randn(*s, dtype=torch.bfloat16) * 0.4)(H, D, M) * ((H * D) ** -0.5)),
        }
    _A_in = _A_setup()

    def _B_setup():
        B, S, D, F = 4, 1, 576, 4608
        return {
            "x": _w((lambda *s: torch.randn(*s, dtype=torch.bfloat16) * 0.05)(B, S, D)),
            "w1": _w((lambda *s: torch.randn(*s, dtype=torch.bfloat16) * 0.05)(S, F) * (S ** -0.5)),
            "b1": _w((lambda *s: torch.randn(*s, dtype=torch.bfloat16) * 0.05)(F) * 0.02),
            "w2": _w((lambda *s: torch.randn(*s, dtype=torch.bfloat16) * 0.05)(F, S) * (F ** -0.5)),
            "b2": _w((lambda *s: torch.randn(*s, dtype=torch.bfloat16) * 0.05)(S) * 0.02),
        }
    _B_in = _B_setup()

    return {
        "A_x": _A_in["x"],
        "A_c_kv": _A_in["c_kv"],
        "A_w_q": _A_in["w_q"],
        "A_w_uk": _A_in["w_uk"],
        "A_w_uv": _A_in["w_uv"],
        "A_w_o": _A_in["w_o"],
        "B_x": _B_in["x"],
        "B_w1": _B_in["w1"],
        "B_b1": _B_in["b1"],
        "B_w2": _B_in["w2"],
        "B_b2": _B_in["b2"],
        "gate_w": _w((lambda *s: torch.randn(*s, dtype=torch.bfloat16) * 0.05)(576) * 16.0),
    }

def reference(A_x, A_c_kv, A_w_q, A_w_uk, A_w_uv, A_w_o, B_x, B_w1, B_b1, B_w2, B_b2, gate_w):
    def _A_ref(x, c_kv, w_q, w_uk, w_uv, w_o):
        B, Sq, M = x.shape[0], x.shape[1], x.shape[2]
        Sk = c_kv.shape[1]
        H, D = w_q.shape[1], w_q.shape[2]
        q = torch.einsum("bqm,mhd->bhqd", x, w_q)
        k = torch.einsum("bkc,chd->bhkd", c_kv, w_uk)
        v = torch.einsum("bkc,chd->bhkd", c_kv, w_uv)
        scores = torch.einsum("bhqd,bhkd->bhqk", q, k) * (D ** -0.5)
        off = Sk - Sq
        qi = torch.arange(Sq)[:, None]
        kj = torch.arange(Sk)[None, :]
        cmask = kj <= (qi + off)
        scores = torch.where(cmask[None, None], scores, -1e9)
        p = _softmax(scores, axis=-1)
        ctx = torch.einsum("bhqk,bhkd->bhqd", p, v)
        return torch.einsum("bhqd,hdm->bqm", ctx, w_o)

    def _B_ref(x, w1, b1, w2, b2):
        B, S, D = x.shape
        h = _layernorm(x, axis=-1)
        u = torch.einsum("bsd,sf->bdf", h, w1) + b1
        u = _gelu(u)
        y = torch.einsum("bdf,fs->bds", u, w2) + b2
        return (lambda x, *d: x.permute(*d))(y, 0, 2, 1)

    x = A_x
    g = _sigmoid((x * gate_w).sum(-1, keepdims=True))
    a = _A_ref(x, A_c_kv, A_w_q, A_w_uk, A_w_uv, A_w_o)
    b = _B_ref(x, B_w1, B_b1, B_w2, B_b2)
    return g * a + (1 - g) * b
```

```cpp
#include <cuda_runtime.h>
#include <cuda_bf16.h>
#include <cuda.h>
#include <stdint.h>

namespace gm {

constexpr int DM = 576;
constexpr int NCTA = 128;
constexpr int NTHREADS = 448;
constexpr int SPIN_LIMIT = 1 << 22;
#define GM_MLPN 72
#define GM_BACKOFF()
#define GM_BARSLEEP 250
#define GM_W1 4
#define GM_WC 4
#define GM_WD 1
#define GM_WT 4

constexpr uint32_t OFF_C = 0;
constexpr uint32_t OFF_A = 131072;
constexpr uint32_t OFF_X0 = OFF_A + 16384;
constexpr uint32_t OFF_B = OFF_A + 36864;
constexpr uint32_t OFF_P = OFF_B + 32768;
constexpr uint32_t OFF_X2 = OFF_P + 8192;
constexpr uint32_t OFF_VB = OFF_X2 + 8192;
constexpr uint32_t OFF_VB2 = OFF_VB + 2176;
constexpr uint32_t OFF_WMAX = OFF_VB2 + 2176;
constexpr uint32_t OFF_WSUM = OFF_WMAX + 2048;
constexpr uint32_t OFF_MLP = OFF_WSUM + 1024;
constexpr uint32_t OFF_COEF = OFF_MLP + 2304;
constexpr uint32_t OFF_GATE = OFF_COEF + 2304;
constexpr uint32_t OFF_X = OFF_X2;
constexpr uint32_t OFF_GW = OFF_X + 4608;
constexpr uint32_t OFF_W1 = OFF_GW + 1152;
constexpr uint32_t OFF_BAR = OFF_GATE + 16;
constexpr uint32_t SMEM_USED = OFF_BAR + 41 * 8;
constexpr uint32_t SMEM_BYTES = SMEM_USED + 1024 + 512;
static_assert(SMEM_BYTES <= 232448, "shared memory");

enum { BAR_WQ = 0, BAR_WUK = 4, BAR_C = 8, BAR_WUV = 24, BAR_WO = 28, BAR_X = 32, BAR_BFREE = 36, BAR_CFREE = 37, BAR_GO = 38, BAR_IN = 40 };
enum { NB_INIT = 0, NB_MAIN = 1, NB_MLP = 2, NB_O = 3, NB_SUM = 4, NB_Q = 6 };

struct Scratch {
    float e1[32][4][128][4];
    uint32_t qabs[4][8][32][32];
    uint32_t part[32][4][4][16][64];
    float2 ml[32][4][16];
    float e4[32][4][4][128];
    float e5[72][32][32];
};
constexpr int EARLY_VEC = (sizeof(Scratch::e1) + sizeof(Scratch::qabs)) / 16;
constexpr int RESET_VEC = (sizeof(Scratch) / 16 - EARLY_VEC) / NCTA;
static_assert(EARLY_VEC == NCTA * 192, "early buffers: 6 vectors per lane");
static_assert((sizeof(Scratch) / 16 - EARLY_VEC) % NCTA == 0, "scratch must split evenly");

__device__ __align__(1024) Scratch g_scratch;
__device__ __align__(128) unsigned int g_arrive[2][32];

#define TS(i)
#define TSIF(c, i)
#define CK32(var, dep)
#define CKST(c, i, v)
#define TS_END()

struct Maps { CUtensorMap wq, wuk, ckv, wuv, wo; };

__device__ __forceinline__ uint32_t smem_u32(const void* p) { return (uint32_t)__cvta_generic_to_shared(p); }
__device__ __forceinline__ void mbar_init(uint32_t bar, int cnt) {
    asm volatile("mbarrier.init.shared::cta.b64 [%0], %1;" ::"r"(bar), "r"(cnt) : "memory");
}
__device__ __forceinline__ void mbar_expect(uint32_t bar, uint32_t bytes) {
    asm volatile("mbarrier.arrive.expect_tx.shared::cta.b64 _, [%0], %1;" ::"r"(bar), "r"(bytes) : "memory");
}
__device__ __forceinline__ void mbar_arrive(uint32_t bar) {
    asm volatile("mbarrier.arrive.shared::cta.b64 _, [%0];" ::"r"(bar) : "memory");
}
__device__ __forceinline__ void mbar_wait(uint32_t bar) {
    uint32_t ok;
    int it = 0;
    do {
        asm volatile("{ .reg .pred p; mbarrier.try_wait.parity.shared::cta.b64 p, [%1], 0; selp.u32 %0, 1, 0, p; }"
                     : "=r"(ok) : "r"(bar) : "memory");
        if (++it > SPIN_LIMIT) __trap();
    } while (!ok);
}
__device__ __forceinline__ uint32_t map_peer(uint32_t addr, uint32_t rank) {
    uint32_t r; asm("mapa.shared::cluster.u32 %0, %1, %2;" : "=r"(r) : "r"(addr), "r"(rank)); return r;
}
__device__ __forceinline__ void st_async4(uint32_t addr, float a, float b, float c, float d, uint32_t bar) {
    asm volatile("st.async.weak.shared::cluster.mbarrier::complete_tx::bytes.v4.f32 [%0], {%1,%2,%3,%4}, [%5];"
                 ::"r"(addr), "f"(a), "f"(b), "f"(c), "f"(d), "r"(bar) : "memory");
}
__device__ __forceinline__ bool mbar_test(uint32_t bar) {
    uint32_t ok;
    asm volatile("{ .reg .pred p; mbarrier.test_wait.parity.shared::cta.b64 p, [%1], 0; selp.u32 %0, 1, 0, p; }"
                 : "=r"(ok) : "r"(bar) : "memory");
    return ok;
}
__device__ __forceinline__ bool elect_one() {
    uint32_t r;
    asm volatile("{ .reg .pred p; elect.sync _|p, 0xffffffff; selp.u32 %0, 1, 0, p; }" : "=r"(r));
    return r;
}
__device__ __forceinline__ bool nb_sync_any(int id, int n, bool v) {
    uint32_t r;
    asm volatile("{ .reg .pred p, q; setp.ne.u32 p, %3, 0; bar.red.or.pred q, %1, %2, p; selp.u32 %0, 1, 0, q; }"
                 : "=r"(r) : "r"(id), "r"(n), "r"((uint32_t)v) : "memory");
    return r;
}
__device__ __forceinline__ void nb_sync(int id, int n) { asm volatile("bar.sync %0, %1;" ::"r"(id), "r"(n) : "memory"); }
__device__ __forceinline__ void nb_arrive(int id, int n) { asm volatile("bar.arrive %0, %1;" ::"r"(id), "r"(n) : "memory"); }
__device__ __forceinline__ void fence_async_smem() { asm volatile("fence.proxy.async.shared::cta;" ::: "memory"); }

__device__ __forceinline__ void tma3d(uint32_t dst, const CUtensorMap* m, int c0, int c1, int c2, uint32_t bar, uint64_t pol) {
    asm volatile("cp.async.bulk.tensor.3d.shared::cluster.global.mbarrier::complete_tx::bytes.L2::cache_hint"
                 " [%0], [%1, {%3, %4, %5}], [%2], %6;"
                 ::"r"(dst), "l"(m), "r"(bar), "r"(c0), "r"(c1), "r"(c2), "l"(pol) : "memory");
}

__device__ __forceinline__ void bulk_load(uint32_t dst, const void* src, uint32_t bytes, uint32_t bar) {
    asm volatile("cp.async.bulk.shared::cluster.global.mbarrier::complete_tx::bytes [%0], [%1], %2, [%3];"
                 ::"r"(dst), "l"(src), "r"(bytes), "r"(bar) : "memory");
}
__device__ __forceinline__ uint32_t lds32(uint32_t a) { uint32_t v; asm volatile("ld.shared.u32 %0, [%1];" : "=r"(v) : "r"(a) : "memory"); return v; }
__device__ __forceinline__ float lds_bf16(uint32_t a) {
    unsigned short v; asm volatile("ld.shared.u16 %0, [%1];" : "=h"(v) : "r"(a) : "memory"); return __uint_as_float((uint32_t)v << 16);
}
__device__ __forceinline__ void ldsm4(uint32_t (&r)[4], uint32_t a) {
    asm volatile("ldmatrix.sync.aligned.m8n8.x4.shared.b16 {%0,%1,%2,%3}, [%4];"
                 : "=r"(r[0]), "=r"(r[1]), "=r"(r[2]), "=r"(r[3]) : "r"(a) : "memory");
}
__device__ __forceinline__ void ldsm4t(uint32_t (&r)[4], uint32_t a) {
    asm volatile("ldmatrix.sync.aligned.m8n8.x4.trans.shared.b16 {%0,%1,%2,%3}, [%4];"
                 : "=r"(r[0]), "=r"(r[1]), "=r"(r[2]), "=r"(r[3]) : "r"(a) : "memory");
}
__device__ __forceinline__ void stsm4t(uint32_t a, uint32_t r0, uint32_t r1, uint32_t r2, uint32_t r3) {
    asm volatile("stmatrix.sync.aligned.m8n8.x4.trans.shared.b16 [%0], {%1,%2,%3,%4};"
                 ::"r"(a), "r"(r0), "r"(r1), "r"(r2), "r"(r3) : "memory");
}
__device__ __forceinline__ void mma16816(float (&d)[4], const uint32_t (&a)[4], uint32_t b0, uint32_t b1) {
    asm volatile("mma.sync.aligned.m16n8k16.row.col.f32.bf16.bf16.f32 {%0,%1,%2,%3}, {%4,%5,%6,%7}, {%8,%9}, {%0,%1,%2,%3};"
                 : "+f"(d[0]), "+f"(d[1]), "+f"(d[2]), "+f"(d[3])
                 : "r"(a[0]), "r"(a[1]), "r"(a[2]), "r"(a[3]), "r"(b0), "r"(b1));
}

__device__ __forceinline__ uint32_t gdesc(uint32_t addr) { return ((addr & 0x3FFFF) >> 4) | (1u << 16); }
__device__ __forceinline__ void wg_fence() { asm volatile("wgmma.fence.sync.aligned;" ::: "memory"); }
__device__ __forceinline__ void wg_commit() { asm volatile("wgmma.commit_group.sync.aligned;" ::: "memory"); }
template <int N> __device__ __forceinline__ void wg_wait() { asm volatile("wgmma.wait_group.sync.aligned %0;" ::"n"(N) : "memory"); }
template <int TA>
__device__ __forceinline__ void wgmma32(float (&d)[16], uint32_t da, uint32_t db) {
    asm volatile("{\n.reg .b64 da, db;\nmov.b64 da, {%16, 0x40000040};\nmov.b64 db, {%17, 0x40000040};\n"
                 "wgmma.mma_async.sync.aligned.m64n32k16.f32.bf16.bf16 "
                 "{%0,%1,%2,%3,%4,%5,%6,%7,%8,%9,%10,%11,%12,%13,%14,%15}, da, db, 1, 1, 1, %18, 0;\n}"
                 : "+f"(d[0]), "+f"(d[1]), "+f"(d[2]), "+f"(d[3]), "+f"(d[4]), "+f"(d[5]), "+f"(d[6]), "+f"(d[7]),
                   "+f"(d[8]), "+f"(d[9]), "+f"(d[10]), "+f"(d[11]), "+f"(d[12]), "+f"(d[13]), "+f"(d[14]), "+f"(d[15])
                 : "r"(da), "r"(db), "n"(TA));
}
__device__ __forceinline__ void reg_fence(float (&d)[16]) {
#pragma unroll
    for (int i = 0; i < 16; i++) asm volatile("" : "+f"(d[i])::"memory");
}

__device__ __forceinline__ uint32_t ld_rlx(const void* p) {
    uint32_t v; asm volatile("ld.relaxed.gpu.global.u32 %0, [%1];" : "=r"(v) : "l"(p) : "memory"); return v;
}
__device__ __forceinline__ uint2 ld_rlx2(const void* p) {
    uint2 v; asm volatile("ld.relaxed.gpu.global.v2.u32 {%0,%1}, [%2];" : "=r"(v.x), "=r"(v.y) : "l"(p) : "memory"); return v;
}
__device__ __forceinline__ uint4 ld_rlx4(const void* p) {
    uint4 v; asm volatile("ld.relaxed.gpu.global.v4.u32 {%0,%1,%2,%3}, [%4];" : "=r"(v.x), "=r"(v.y), "=r"(v.z), "=r"(v.w) : "l"(p) : "memory"); return v;
}
__device__ __forceinline__ void st_rlx(void* p, uint32_t v) { asm volatile("st.relaxed.gpu.global.u32 [%0], %1;" ::"l"(p), "r"(v) : "memory"); }
__device__ __forceinline__ void st_rlx2(void* p, uint32_t a, uint32_t b) {
    asm volatile("st.relaxed.gpu.global.v2.u32 [%0], {%1,%2};" ::"l"(p), "r"(a), "r"(b) : "memory");
}
__device__ __forceinline__ uint32_t nz(uint32_t v) { return v == 0u ? 0x80000000u : v; }
__device__ __forceinline__ uint32_t nzf(float v) { return nz(__float_as_uint(v)); }
__device__ __forceinline__ bool full2(const uint2& v) { return v.x != 0u && v.y != 0u; }
__device__ __forceinline__ bool full4(const uint4& v) { return v.x != 0u && v.y != 0u && v.z != 0u && v.w != 0u; }

__device__ __forceinline__ uint32_t pack_bf16(float lo, float hi) {
    uint32_t r; asm("cvt.rn.bf16x2.f32 %0, %1, %2;" : "=r"(r) : "f"(hi), "f"(lo)); return r;
}
__device__ __forceinline__ float bf_lo(uint32_t v) { return __uint_as_float(v << 16); }
__device__ __forceinline__ float bf_hi(uint32_t v) { return __uint_as_float(v & 0xFFFF0000u); }
__device__ __forceinline__ float ex2(float x) { float r; asm("ex2.approx.ftz.f32 %0, %1;" : "=f"(r) : "f"(x)); return r; }
__device__ __forceinline__ float tanh_fast(float x) { float r; asm("tanh.approx.f32 %0, %1;" : "=f"(r) : "f"(x)); return r; }
__device__ __forceinline__ void sts32(uint32_t a, uint32_t v) { asm volatile("st.shared.u32 [%0], %1;" ::"r"(a), "r"(v) : "memory"); }
__device__ __forceinline__ void sts16(uint32_t a, uint32_t v) { asm volatile("st.shared.u16 [%0], %1;" ::"r"(a), "h"((unsigned short)v) : "memory"); }
__device__ __forceinline__ void stsf(uint32_t a, float v) { asm volatile("st.shared.f32 [%0], %1;" ::"r"(a), "f"(v) : "memory"); }
__device__ __forceinline__ float ldsf(uint32_t a) { float v; asm volatile("ld.shared.f32 %0, [%1];" : "=f"(v) : "r"(a) : "memory"); return v; }
__device__ __forceinline__ float4 ldsf4(uint32_t a) {
    float4 v; asm volatile("ld.shared.v4.f32 {%0,%1,%2,%3}, [%4];" : "=f"(v.x), "=f"(v.y), "=f"(v.z), "=f"(v.w) : "r"(a) : "memory"); return v;
}
__device__ __forceinline__ float max4(const float4& v) { return fmaxf(fmaxf(v.x, v.y), fmaxf(v.z, v.w)); }
__device__ __forceinline__ float sum4(const float4& v) { return (v.x + v.y) + (v.z + v.w); }

template <bool IS_MAX>
__device__ __forceinline__ float reduce_heads(float (&v)[8], int lane) {
    auto op = [](float a, float b) { return IS_MAX ? fmaxf(a, b) : a + b; };
    const bool up16 = lane & 16, up8 = lane & 8, up4 = lane & 4;
    float a[4], b[2];
#pragma unroll
    for (int i = 0; i < 4; i++) {
        float send = up16 ? v[i] : v[i + 4], keep = up16 ? v[i + 4] : v[i];
        a[i] = op(keep, __shfl_xor_sync(0xffffffffu, send, 16));
    }
#pragma unroll
    for (int i = 0; i < 2; i++) {
        float send = up8 ? a[i] : a[i + 2], keep = up8 ? a[i + 2] : a[i];
        b[i] = op(keep, __shfl_xor_sync(0xffffffffu, send, 8));
    }
    float send = up4 ? b[0] : b[1], keep = up4 ? b[1] : b[0];
    return op(keep, __shfl_xor_sync(0xffffffffu, send, 4));
}

__device__ __forceinline__ void fold_hilo(const float (&d)[4], int t, float& v0, float& v1) {
    const bool up = t & 2;
    float s0 = up ? d[0] : d[2], s1 = up ? d[1] : d[3];
    float k0 = up ? d[2] : d[0], k1 = up ? d[3] : d[1];
    v0 = k0 + __shfl_xor_sync(0xffffffffu, s0, 2);
    v1 = k1 + __shfl_xor_sync(0xffffffffu, s1, 2);
}

template <typename T> __device__ __forceinline__ void pin(T*& p) { asm volatile("" : "+l"(p)); }
__device__ __forceinline__ void pin(uint32_t& v) { asm volatile("" : "+r"(v)); }

constexpr float REF_SLACK = 32.f;
__device__ __forceinline__ void attention(const uint32_t sb, const int rank, const int wg, const int wp, const int lane,
                                          float (&acc)[2][16], float2* ml_dst) {
    const uint32_t bar = sb + OFF_BAR;
    const int g = lane >> 2, t = lane & 3;
    const int myhead = 8 * (g >> 1) + 2 * t + (g & 1);
    float mref[8], ls[8], s[16];
    uint32_t pk[8];
#pragma unroll
    for (int i = 0; i < 16; i++) acc[0][i] = acc[1][i] = 0.f;
#pragma unroll
    for (int i = 0; i < 8; i++) mref[i] = ls[i] = 0.f;
    const uint32_t dq = gdesc(sb + OFF_A), dp = gdesc(sb + OFF_P), dc0 = gdesc(sb + OFF_C);
    uint32_t xloc = sb + (wp * 32 + lane) * 16;
    uint32_t xrem = map_peer(xloc, rank ^ 1), xbar = map_peer(bar + 8 * BAR_X, rank ^ 1);
    uint32_t wmax_st = sb + OFF_WMAX + myhead * 16 + wp * 4, wmax_ld = sb + OFF_WMAX + t * 32;
    uint32_t p_st = sb + OFF_P + wg * 4096 + (8 * (lane >> 4) + (lane & 7)) * 128 + (((2 * wp + ((lane >> 3) & 1)) ^ (lane & 7)) << 4);
    uint32_t wsum = sb + OFF_WSUM + myhead * 32;
    pin(xloc); pin(xrem); pin(xbar); pin(wmax_st); pin(wmax_ld); pin(p_st); pin(wsum);
    auto xoff = [](int tile) { return tile == 2 ? OFF_X2 : OFF_X0 + (tile == 1 ? 8192u : 0u); };
    auto write_p = [&]() {
#pragma unroll
        for (int jj = 0; jj < 4; jj++) {
            pk[2 * jj] = pack_bf16(ex2(s[4 * jj]), ex2(s[4 * jj + 1]));
            pk[2 * jj + 1] = pack_bf16(ex2(s[4 * jj + 2]), ex2(s[4 * jj + 3]));
        }
        stsm4t(p_st, pk[0], pk[1], pk[2], pk[3]);
        stsm4t(p_st + 2048, pk[4], pk[5], pk[6], pk[7]);
        fence_async_smem();
    };
#pragma unroll 1
    for (int st = -2; st < 4; st++) {
        const bool mine = wg == (st & 1);
        if (st >= 0) {
            bool redo = st == 0;
            if (mine) {
#pragma unroll
                for (int i = 0; i < 16; i++) s[i] -= mref[2 * (i >> 2) + (i & 1)];
                const uint32_t xa = xloc + xoff(st);
                mbar_wait(bar + 8 * (BAR_X + st));
#pragma unroll
                for (int i = 0; i < 4; i++) {
                    const float4 r = ldsf4(xa + i * 2048);
                    s[4 * i] += r.x; s[4 * i + 1] += r.y; s[4 * i + 2] += r.z; s[4 * i + 3] += r.w;
                }
                TSIF(lane == 0 && wp == 0, 20 + st);
            }
            if (!redo) {
                bool bad = false;
                CK32(q0, 0);
                if (mine) {
                    write_p();
                    float m = s[0];
#pragma unroll
                    for (int i = 1; i < 16; i++) m = fmaxf(m, s[i]);
                    bad = m > REF_SLACK;
                }
                CK32(q1, 0);
                redo = nb_sync_any(NB_MAIN, 256, bad);
                CK32(q2, 0);
                CKST(lane == 0 && wp == 0 && st == 3 && mine, 56, q1 - q0); CKST(lane == 0 && wp == 0 && st == 3 && mine, 57, q2 - q1);
            }
            if (redo) {
                if (mine) {
                    float mx[8];
#pragma unroll
                    for (int i = 0; i < 4; i++) {
                        mx[2 * i] = fmaxf(s[4 * i], s[4 * i + 2]);
                        mx[2 * i + 1] = fmaxf(s[4 * i + 1], s[4 * i + 3]);
                    }
                    stsf(wmax_st + st * 512, reduce_heads<true>(mx, lane));
                }
                nb_sync(NB_MAIN, 256);
#pragma unroll
                for (int i = 0; i < 8; i++) {
                    float d = max4(ldsf4(wmax_ld + st * 512 + (8 * (i >> 1) + (i & 1)) * 16));
                    if (st > 0) d = fmaxf(d, 0.f);
                    mref[i] += d;
                    const float al = ex2(fminf(-d, 0.f));
                    ls[i] *= al;
                    const int r = 4 * (i >> 1) + (i & 1);
                    acc[0][r] *= al; acc[0][r + 2] *= al; acc[1][r] *= al; acc[1][r + 2] *= al;
                    if (mine) { s[r] -= d; s[r + 2] -= d; }
                }
                if (mine) write_p();
                reg_fence(acc[0]);
                reg_fence(acc[1]);
                nb_sync(NB_MAIN, 256);
            }
            const uint32_t dpt = dp + (st & 1) * 256, dct = dc0 + st * 2048 + wg * 1024;
            CK32(p0, 0);
            wg_fence();
#pragma unroll
            for (int T = 0; T < 2; T++)
#pragma unroll
                for (int k = 0; k < 4; k++) wgmma32<1>(acc[T], dct + T * 512 + k * 128, dpt + k * 2);
            wg_commit();
            if (mine) {
#pragma unroll
                for (int jj = 0; jj < 4; jj++) {
                    ls[2 * jj] += bf_lo(pk[2 * jj]) + bf_lo(pk[2 * jj + 1]);
                    ls[2 * jj + 1] += bf_hi(pk[2 * jj]) + bf_hi(pk[2 * jj + 1]);
                }
            }
            if (st == 3) stsf(wsum + (4 * wg + wp) * 4, reduce_heads<false>(ls, lane));
            CK32(p1, 0);
            wg_wait<0>();
            reg_fence(acc[0]);
            reg_fence(acc[1]);
            CK32(p2, 0);
            CKST(lane == 0 && wp == 0 && st == 2, 52 + 2 * wg, p1 - p0); CKST(lane == 0 && wp == 0 && st == 2, 53 + 2 * wg, p2 - p1);
            if (st == 1 && lane == 0) mbar_arrive(bar + 8 * BAR_CFREE);
            TSIF(lane == 0 && wp == 0 && wg == 0, 24 + st);
        }
        if (mine && st < 2) {
            const int tile = st + 2;
            const uint32_t dc = dc0 + tile * 2048;
            CK32(k0, 0);
#pragma unroll
            for (int i = 0; i < 16; i++) s[i] = 0.f;
#pragma unroll
            for (int q = 0; q < 4; q++) {
                mbar_wait(bar + 8 * (BAR_C + tile * 4 + q));
                reg_fence(s);
                wg_fence();
#pragma unroll
                for (int k = 0; k < 4; k++) wgmma32<0>(s, dc + q * 512 + k * 2, dq + q * 256 + k * 2);
                wg_commit();
            }
            const uint32_t xa = xrem + xoff(tile), xb = xbar + 8 * tile;
            CK32(k1, 0);
            wg_wait<0>();
            reg_fence(s);
            CK32(k2, 0);
            CKST(lane == 0 && wp == 0 && tile == 2, 50, k1 - k0); CKST(lane == 0 && wp == 0 && tile == 2, 51, k2 - k1);
#pragma unroll
            for (int i = 0; i < 4; i++) st_async4(xa + i * 2048, s[4 * i], s[4 * i + 1], s[4 * i + 2], s[4 * i + 3], xb);
            TSIF(lane == 0 && wp == 0, 16 + tile);
        }
    }
    mbar_wait(bar + 8 * (BAR_GO + 1));
    if (wg == 0 && wp == 0) {
        nb_sync(NB_SUM, 256);
        const float l = sum4(ldsf4(wsum)) + sum4(ldsf4(wsum + 16));
        const float m01 = (g & 1) ? mref[1] : mref[0], m23 = (g & 1) ? mref[3] : mref[2];
        const float m45 = (g & 1) ? mref[5] : mref[4], m67 = (g & 1) ? mref[7] : mref[6];
        const float m = (g & 4) ? ((g & 2) ? m67 : m45) : ((g & 2) ? m23 : m01);
        if (rank == 0) st_rlx2(ml_dst, nzf(m), nzf(l));
    } else {
        nb_arrive(NB_SUM, 256);
    }
}

__global__ void __cluster_dims__(2, 1, 1) __launch_bounds__(NTHREADS, 1)
gated_mix_kernel(const __grid_constant__ Maps maps, const __nv_bfloat16* __restrict__ x,
                 const __nv_bfloat16* __restrict__ w1, const __nv_bfloat16* __restrict__ b1,
                 const __nv_bfloat16* __restrict__ w2, const __nv_bfloat16* __restrict__ b2,
                 const __nv_bfloat16* __restrict__ gate_w, __nv_bfloat16* __restrict__ out) {
    extern __shared__ __align__(1024) unsigned char smem_raw[];
    const uint32_t sb = (smem_u32(smem_raw) + 1023u) & ~1023u;
    const uint32_t bar = sb + OFF_BAR;
    const int tid = threadIdx.x, lane = tid & 31;
    const int warp = __shfl_sync(0xffffffffu, tid >> 5, 0);
    const int cta = blockIdx.x, h = cta >> 2, j = cta & 3;
    const int rank = cta & 1, bq = cta >> 5, split = (cta >> 1) & 15;
    const int g = lane >> 2, t = lane & 3, lr = lane & 7, li = lane >> 3;
    Scratch& S = g_scratch;
    uint32_t ao[8][4];
    bool have_o = false;
    const uint32_t awo = sb + OFF_C + (lr + 8 * (li >> 1)) * 304 + (2 * warp + (li & 1)) * 16;

    if (warp == 12) {
        uint64_t pol;
        asm volatile("createpolicy.fractional.L2::evict_first.b64 %0, 1.0;" : "=l"(pol));
        const bool leader = elect_one();
        if (leader) {
            TS(0);
#pragma unroll
            for (int i = 0; i < 4; i++) mbar_init(bar + 8 * i, 1);
            asm volatile("fence.mbarrier_init.release.cluster;" ::: "memory");
#pragma unroll
            for (int q = 0; q < 4; q++) {
                mbar_expect(bar + 8 * q, 9216);
                tma3d(sb + OFF_A + (q & 1) * 18432 + (q >> 1) * 9216, &maps.wq, 0, j * 144 + (q >> 1) * 72, 2 * h + (q & 1), bar + 8 * q, pol);
                TSIF(q == 0, 1);
            }
        }
        __syncwarp();
        nb_sync(NB_INIT, 448);
        if (leader) {
            auto window = [&](int i, int w) { mbar_wait(bar + 8 * (i - w)); TSIF(((i - w) & 3) == 3, 40 + ((i - w) >> 2)); };
            auto weights = [&](const CUtensorMap* m, int first, int w) {
#pragma unroll 1
                for (int q = 0; q < 4; q++) {
                    const int i = first + q;
                    if (i >= w && (first != BAR_WUV || q + 1 > w - GM_WD)) window(i, w);
                    mbar_expect(bar + 8 * i, 8192);
                    tma3d(sb + OFF_B + (q & 1) * 16384 + (q >> 1) * 8192, m, 0, j * 128 + (q >> 1) * 64, 2 * h + (q & 1), bar + 8 * i, pol);
                }
            };
            weights(&maps.wuk, BAR_WUK, GM_W1);
#pragma unroll 1
            for (int q = 0; q < 16; q++) {
                const int i = BAR_C + q;
                if (i >= GM_WC && (i - GM_WC >= BAR_C - GM_W1)) window(i, GM_WC);
                mbar_expect(bar + 8 * i, 8192);
                tma3d(sb + OFF_C + q * 8192, &maps.ckv, 0, (cta >> 1) * 256 + (q >> 2) * 64, 4 * rank + (q & 3), bar + 8 * i, pol);
            }
#pragma unroll 1
            for (int k = BAR_WUV - GM_WC; k <= BAR_WUV - GM_WD; k++) window(k, 0);
            mbar_wait(bar + 8 * BAR_BFREE);
            weights(&maps.wuv, BAR_WUV, GM_WT);
            mbar_wait(bar + 8 * BAR_CFREE);
#pragma unroll 1
            for (int q = 0; q < 4; q++) {
                const int i = BAR_WO + q;
                window(i, GM_WT);
                mbar_expect(bar + 8 * i, 9728);
                tma3d(sb + OFF_C + q * 9728, &maps.wo, j * 144, h * 128 + q * 32, 0, bar + 8 * i, pol);
            }
        }
        TS_END();
        return;
    }
    if (warp == 13) {
        auto zero = [&](uint4* z, int n) {
#pragma unroll 6
            for (int i = lane; i < n; i += 32)
                asm volatile("st.relaxed.gpu.global.v4.u32 [%0], {%1,%1,%1,%1};" ::"l"(z + i), "r"(0u) : "memory");
            __syncwarp();
        };
        auto arrive = [&](unsigned* ctr) {
            unsigned old = 0;
            if (lane == 0) asm volatile("atom.add.release.gpu.global.u32 %0, [%1], 1;" : "=r"(old) : "l"(ctr) : "memory");
            return (old & ~(unsigned)(NCTA - 1)) + NCTA;
        };
        auto wait_all = [&](const unsigned* ctr, unsigned target, int go) {
            if (lane == 0) {
                int it = 0;
                while (true) {
                    unsigned v;
                    asm volatile("ld.acquire.gpu.global.u32 %0, [%1];" : "=r"(v) : "l"(ctr) : "memory");
                    if ((int)(v - target) >= 0) break;
                    if (++it > SPIN_LIMIT) __trap();
                    __nanosleep(GM_BARSLEEP);
                }
                mbar_arrive(bar + 8 * (BAR_GO + go));
                TS(10 + go);
            }
            __syncwarp();
        };
        if (elect_one()) {
            mbar_init(bar + 8 * BAR_IN, 1);
            asm volatile("fence.mbarrier_init.release.cluster;" ::: "memory");
            mbar_expect(bar + 8 * BAR_IN, 4608 + 1152 + 864);
            bulk_load(sb + OFF_X, x, 4608, bar + 8 * BAR_IN);
            bulk_load(sb + OFF_GW, gate_w, 1152, bar + 8 * BAR_IN);
            bulk_load(sb + OFF_W1, w1 + h * 144, 288, bar + 8 * BAR_IN);
            bulk_load(sb + OFF_W1 + 288, b1 + h * 144, 288, bar + 8 * BAR_IN);
            bulk_load(sb + OFF_W1 + 576, w2 + h * 144, 288, bar + 8 * BAR_IN);
        }
        __syncwarp();
        zero(reinterpret_cast<uint4*>(&S) + cta * 192, 192);
        nb_sync(NB_INIT, 448);
        const unsigned target0 = arrive(&g_arrive[0][0]);
        TSIF(lane == 0, 9);
        wait_all(&g_arrive[0][0], target0, 0);
#define GM_RESET_AFTER (BAR_WUK + 3)
        mbar_wait(bar + 8 * GM_RESET_AFTER);
        zero(reinterpret_cast<uint4*>(&S) + EARLY_VEC + cta * RESET_VEC, RESET_VEC);
        const unsigned target1 = arrive(&g_arrive[1][0]);
        wait_all(&g_arrive[1][0], target1, 1);
        TS_END();
        return;
    }

    if (warp >= 8) {
        const int b = warp - 8, mt = tid - 256;
        uint32_t xv[9], gv[9];
        float hv[9], acc[9];
        const float bias2 = (h == 0 && lane < 16) ? __bfloat162float(b2[0]) : 0.f;
        nb_sync(NB_INIT, 448);
        mbar_wait(bar + 8 * BAR_IN);
#pragma unroll
        for (int k = 0; k < 9; k++) {
            xv[k] = lds32(sb + OFF_X + b * (DM * 2) + (lane + 32 * k) * 4);
            gv[k] = lds32(sb + OFF_GW + (lane + 32 * k) * 4);
            hv[k] = lds_bf16(sb + OFF_X + (b * DM + j * 144 + (lane & 15) + 16 * k) * 2);
        }
        for (int f = mt; f < 144; f += 128) {
            stsf(sb + OFF_COEF + f * 16, lds_bf16(sb + OFF_W1 + f * 2));
            stsf(sb + OFF_COEF + f * 16 + 4, lds_bf16(sb + OFF_W1 + 288 + f * 2));
            stsf(sb + OFF_COEF + f * 16 + 8, 0.5f * lds_bf16(sb + OFF_W1 + 576 + f * 2));
        }
        float sum = 0.f, z = 0.f;
#pragma unroll
        for (int k = 0; k < 9; k++) {
            sum += bf_lo(xv[k]) + bf_hi(xv[k]);
            z = fmaf(bf_lo(xv[k]), bf_lo(gv[k]), fmaf(bf_hi(xv[k]), bf_hi(gv[k]), z));
        }
#pragma unroll
        for (int o = 16; o; o >>= 1) {
            sum += __shfl_xor_sync(0xffffffffu, sum, o);
            z += __shfl_xor_sync(0xffffffffu, z, o);
        }
        const float mean = sum * (1.f / DM);
        float var = 0.f;
#pragma unroll
        for (int k = 0; k < 9; k++) {
            const float d0 = bf_lo(xv[k]) - mean, d1 = bf_hi(xv[k]) - mean;
            var = fmaf(d0, d0, fmaf(d1, d1, var));
        }
#pragma unroll
        for (int o = 16; o; o >>= 1) var += __shfl_xor_sync(0xffffffffu, var, o);
        const float rstd = 1.f / sqrtf(var * (1.f / DM) + 1e-5f);
        const float gate = 1.f / (1.f + __expf(-z));
        if (lane == 0) stsf(sb + OFF_GATE + b * 4, gate);
#pragma unroll
        for (int k = 0; k < 9; k++) { hv[k] = (hv[k] - mean) * rstd; acc[k] = 0.f; }
        nb_arrive(NB_Q, 384);
        nb_sync(NB_MLP, 128);
        TSIF(mt == 0, 3);
        float p0 = 0.f, p1 = bias2;
        const uint32_t ca = sb + OFF_COEF + (lane >> 4) * 72 * 16;
#pragma unroll 2
        for (int f = 0; f < GM_MLPN; f++) {
            const float4 c = ldsf4(ca + f * 16);
            p0 = fmaf(c.x, c.z, p0);
            p1 = fmaf(c.y, c.z, p1);
#pragma unroll
            for (int k = 0; k < 9; k++) {
                const float u = fmaf(hv[k], c.x, c.y);
                const float in = u * fmaf(u * u, 0.7978845608028654f * 0.044715f, 0.7978845608028654f);
                acc[k] = fmaf(u * c.z, tanh_fast(in), acc[k]);
            }
        }
        const float og = 1.f - gate;
#pragma unroll
        for (int k = 0; k < 9; k++) {
            float v = acc[k] + fmaf(hv[k], p0, p1);
            v += __shfl_xor_sync(0xffffffffu, v, 16);
            if (lane < 16) stsf(sb + OFF_MLP + (b * 144 + lane + 16 * k) * 4, og * v);
        }
        TSIF(mt == 0, 8);
        if (warp >= 10) {
            nb_arrive(NB_O, 384);
            TS_END();
            return;
        }
    } else {
        const int wg = warp >> 2, wp = warp & 3;
        if (elect_one()) {
#pragma unroll
            for (int i = 0; i < 4; i++) mbar_init(bar + 8 * (4 + 4 * warp + i), 1);
            if (warp == 7) {
#pragma unroll
                for (int i = 0; i < 4; i++) mbar_expect(bar + 8 * (BAR_X + i), 8192);
            }
            if (warp < 4) mbar_init(bar + 8 * (BAR_BFREE + warp), warp < 2 ? 8 : 1);
            asm volatile("fence.mbarrier_init.release.cluster;" ::: "memory");
        }
        __syncwarp();
        nb_sync(NB_INIT, 448);

        {
            uint32_t xb[9][2];
            mbar_wait(bar + 8 * BAR_IN);
#pragma unroll
            for (int ks = 0; ks < 9; ks++) {
                const uint32_t px = sb + OFF_X + ((g & 3) * DM + j * 144 + ks * 16) * 2 + t * 4;
                xb[ks][0] = g < 4 ? lds32(px) : 0u;
                xb[ks][1] = g < 4 ? lds32(px + 16) : 0u;
            }
            float d[4] = {0.f, 0.f, 0.f, 0.f};
            const uint32_t a0 = sb + OFF_A + wg * 18432 + (lr + 8 * (li >> 1)) * 128 + (((2 * wp + (li & 1)) ^ lr) << 4);
            mbar_wait(bar + 8 * (BAR_WQ + wg));
            mbar_wait(bar + 8 * (BAR_WQ + 2 + wg));
#pragma unroll
            for (int ks = 0; ks < 9; ks++) {
                uint32_t a[4];
                ldsm4t(a, a0 + ks * 2048);
                mma16816(d, a, xb[ks][0], xb[ks][1]);
            }
            mbar_wait(bar + 8 * BAR_GO);
            if (t < 2) {
                st_rlx2(&S.e1[h][j][16 * warp + g][2 * t], nzf(d[0]), nzf(d[1]));
                st_rlx2(&S.e1[h][j][16 * warp + g + 8][2 * t], nzf(d[2]), nzf(d[3]));
            }
            TSIF(tid == 0, 12);
        }
        {
            const int dd = tid >> 1, bp = tid & 1;
            uint2 v[4];
            int it = 0;
            while (true) {
#pragma unroll
                for (int s = 0; s < 4; s++) v[s] = ld_rlx2(&S.e1[h][s][dd][2 * bp]);
                if (full2(v[0]) && full2(v[1]) && full2(v[2]) && full2(v[3])) break;
                if (++it > SPIN_LIMIT) __trap();
            }
            const float q0 = (__uint_as_float(v[0].x) + __uint_as_float(v[1].x)) + (__uint_as_float(v[2].x) + __uint_as_float(v[3].x));
            const float q1 = (__uint_as_float(v[0].y) + __uint_as_float(v[1].y)) + (__uint_as_float(v[2].y) + __uint_as_float(v[3].y));
            const uint32_t hi = pack_bf16(q0, q1);
            const uint32_t lo = pack_bf16(q0 - bf_lo(hi), q1 - bf_hi(hi));
            const uint32_t a = sb + OFF_VB + (2 * bp) * 272 + dd * 2;
            sts16(a, hi & 0xFFFFu);
            sts16(a + 272, hi >> 16);
            sts16(a + 4 * 272, lo & 0xFFFFu);
            sts16(a + 5 * 272, lo >> 16);
        }
        TSIF(tid == 0, 13);
        const uint4* qsrc;
        uint32_t probe0 = 1u, probe1 = 1u;
        {
            uint32_t a[8][4];
            const uint32_t a0 = sb + OFF_B + (16 * warp + lr + 8 * (li & 1)) * 128;
            qsrc = reinterpret_cast<const uint4*>(&S.qabs[bq][4 * rank][0][0]) + tid;
            mbar_wait(bar + 8 * (BAR_WUK + 2 * wg));
            mbar_wait(bar + 8 * (BAR_WUK + 2 * wg + 1));
#pragma unroll
            for (int ks = 0; ks < 8; ks++) ldsm4(a[ks], a0 + (ks >> 2) * 16384 + (((2 * (ks & 3) + (li >> 1)) ^ lr) << 4));
            nb_sync(NB_Q, 384);
            if (lr == 0) {
                const bool self = (tid >> 3) == h && (j >> 1) == rank;
                if (!(self && (j & 1) == 0)) probe0 = ld_rlx(qsrc);
                if (!(self && (j & 1) == 1)) probe1 = ld_rlx(qsrc + 512);
            }
            float d[4] = {0.f, 0.f, 0.f, 0.f};
#pragma unroll
            for (int i = 0; i < 4; i++) {
                uint32_t bb[4];
                ldsm4(bb, sb + OFF_VB + lr * 272 + (4 * i + li) * 16);
                mma16816(d, a[2 * i], bb[0], bb[1]);
                mma16816(d, a[2 * i + 1], bb[2], bb[3]);
            }
            if (lane == 0) mbar_arrive(bar + 8 * BAR_BFREE);
            float v0, v1;
            fold_hilo(d, t, v0, v1);
            const float sc = 0.08838834764831845f * 1.4426950408889634f;
            v0 *= sc; v1 *= sc;
            const bool odd = g & 1;
            const float got = __shfl_xor_sync(0xffffffffu, odd ? v0 : v1, 4);
            const uint32_t w = odd ? pack_bf16(got, v1) : pack_bf16(v0, got);
            const int bb = 2 * (t & 1) + (odd ? 1 : 0);
            const int cl = 16 * warp + (g & ~1) + 8 * (t >> 1);
            st_rlx(&S.qabs[bb][2 * j + (cl >> 6)][h][((((cl & 63) >> 3) ^ (h & 7)) << 2) + ((cl & 7) >> 1)], nz(w));
        }
        TSIF(tid == 0, 14);
        {
            const uint4* src = qsrc;
            int it = 0;
            while (probe0 == 0u || probe1 == 0u) {
                if (probe0 == 0u) probe0 = ld_rlx(src);
                if (probe1 == 0u) probe1 = ld_rlx(src + 512);
                if (++it > SPIN_LIMIT) __trap();
            }
            __syncwarp();
            uint4 v[4];
#pragma unroll
            for (int i = 0; i < 4; i++) v[i] = ld_rlx4(src + 256 * i);
            while (true) {
                bool ok = true;
#pragma unroll
                for (int i = 0; i < 4; i++)
                    if (!full4(v[i])) { ok = false; v[i] = ld_rlx4(src + 256 * i); }
                if (ok) break;
                if (++it > SPIN_LIMIT) __trap();
            }
#pragma unroll
            for (int i = 0; i < 4; i++)
                asm volatile("st.shared.v4.u32 [%0], {%1,%2,%3,%4};" ::"r"(sb + OFF_A + (tid + 256 * i) * 16), "r"(v[i].x), "r"(v[i].y), "r"(v[i].z), "r"(v[i].w) : "memory");
            fence_async_smem();
            nb_sync(NB_MAIN, 256);
        }
        TSIF(tid == 0, 15);

        uint32_t* part_st = &S.part[2 * t][2 * rank + wg][bq][split][wp * 16 + g * 2];
        const uint4* part_ld = reinterpret_cast<const uint4*>(&S.part[h][j][warp >> 1][li][(warp & 1) * 32 + lr * 4]);
        const float2* ml_ld = &S.ml[h][warp >> 1][lane & 15];
        pin(part_st); pin(part_ld); pin(ml_ld);

        float acc[2][16];
        attention(sb, rank, wg, wp, lane, acc, &S.ml[8 * (g >> 1) + 2 * t + (g & 1)][bq][split]);

        TSIF(tid == 0, 27);
#pragma unroll
        for (int i = 0; i < 8; i++) {
            const int r = 4 * (i >> 1) + (i & 1);
            st_rlx2(part_st + (8 * (i >> 1) + (i & 1)) * (4 * 4 * 16 * 64),
                    nz(pack_bf16(acc[0][r], acc[0][r + 2])), nz(pack_bf16(acc[1][r], acc[1][r + 2])));
        }
        TSIF(tid == 0, 28);

        uint32_t a[8][4];
        {
            const uint32_t auv = sb + OFF_B + wg * 16384 + (lr + 8 * (li >> 1)) * 128 + (((2 * wp + (li & 1)) ^ lr) << 4);
            uint2 mlv;
            int it = 0;
            do {
                mlv = ld_rlx2(ml_ld);
                if (++it > SPIN_LIMIT) __trap();
            } while (!__all_sync(0xffffffffu, full2(mlv)));
            uint4 v[4];
#pragma unroll
            for (int i = 0; i < 4; i++) v[i] = ld_rlx4(part_ld + i * 64);
            const float m = __uint_as_float(mlv.x);
            float M = m;
#pragma unroll
            for (int o = 8; o; o >>= 1) M = fmaxf(M, __shfl_xor_sync(0xffffffffu, M, o));
            const float e = ex2(m - M);
            float L = e * __uint_as_float(mlv.y);
#pragma unroll
            for (int o = 8; o; o >>= 1) L += __shfl_xor_sync(0xffffffffu, L, o);
            const float wgt = e / L;
            float w[4];
#pragma unroll
            for (int i = 0; i < 4; i++) w[i] = __shfl_sync(0xffffffffu, wgt, 4 * i + li);
            const int b = warp >> 1, half = warp & 1;
            const bool u16 = lane & 16, u8 = lane & 8;
            uint32_t vb_st = sb + OFF_VB + b * 272 + ((u16 ? 64 : 0) + 16 * (2 * half + (lr >> 2)) + (u8 ? 8 : 0) + 2 * (lr & 3)) * 2;
            pin(vb_st);
            TSIF(tid == 0, 29);
            bool have = false;
            it = 0;
            while (true) {
                if (!have && mbar_test(bar + 8 * (BAR_WUV + wg)) && mbar_test(bar + 8 * (BAR_WUV + 2 + wg))) {
                    have = true;
#pragma unroll
                    for (int ks = 0; ks < 8; ks++) ldsm4t(a[ks], auv + ks * 2048);
                }
                bool ok = true;
#pragma unroll
                for (int i = 0; i < 4; i++)
                    if (!full4(v[i])) { ok = false; v[i] = ld_rlx4(part_ld + i * 64); }
                if (__all_sync(0xffffffffu, ok)) break;
                if (++it > SPIN_LIMIT) __trap();
            }
            TSIF(tid == 0, 30);
            float c[8];
#pragma unroll
            for (int i = 0; i < 8; i++) c[i] = 0.f;
#pragma unroll
            for (int i = 0; i < 4; i++) {
                c[0] = fmaf(w[i], bf_lo(v[i].x), c[0]); c[1] = fmaf(w[i], bf_hi(v[i].x), c[1]);
                c[2] = fmaf(w[i], bf_lo(v[i].y), c[2]); c[3] = fmaf(w[i], bf_hi(v[i].y), c[3]);
                c[4] = fmaf(w[i], bf_lo(v[i].z), c[4]); c[5] = fmaf(w[i], bf_hi(v[i].z), c[5]);
                c[6] = fmaf(w[i], bf_lo(v[i].w), c[6]); c[7] = fmaf(w[i], bf_hi(v[i].w), c[7]);
            }
            float r0 = (u16 ? c[2] : c[0]) + __shfl_xor_sync(0xffffffffu, u16 ? c[0] : c[2], 16);
            float r1 = (u16 ? c[3] : c[1]) + __shfl_xor_sync(0xffffffffu, u16 ? c[1] : c[3], 16);
            float r2 = (u16 ? c[6] : c[4]) + __shfl_xor_sync(0xffffffffu, u16 ? c[4] : c[6], 16);
            float r3 = (u16 ? c[7] : c[5]) + __shfl_xor_sync(0xffffffffu, u16 ? c[5] : c[7], 16);
            const float y0 = (u8 ? r1 : r0) + __shfl_xor_sync(0xffffffffu, u8 ? r0 : r1, 8);
            const float y1 = (u8 ? r3 : r2) + __shfl_xor_sync(0xffffffffu, u8 ? r2 : r3, 8);
            const uint32_t hi = pack_bf16(y0, y1);
            const uint32_t lo = pack_bf16(y0 - bf_lo(hi), y1 - bf_hi(hi));
            sts32(vb_st, hi);
            sts32(vb_st + 4 * 272, lo);
            if (!have) {
                mbar_wait(bar + 8 * (BAR_WUV + wg));
                mbar_wait(bar + 8 * (BAR_WUV + 2 + wg));
#pragma unroll
                for (int ks = 0; ks < 8; ks++) ldsm4t(a[ks], auv + ks * 2048);
            }
        }
        {
            float* dst = &S.e4[h][j][2 * (t & 1)][16 * warp + g + 8 * (t >> 1)];
            uint32_t vb_ld = sb + OFF_VB + lr * 272 + li * 16;
            pin(dst); pin(vb_ld);
            nb_sync(NB_MAIN, 256);
            TSIF(tid == 0, 31);
            float d0[4] = {0.f, 0.f, 0.f, 0.f}, d1[4] = {0.f, 0.f, 0.f, 0.f};
#pragma unroll
            for (int i = 0; i < 4; i++) {
                uint32_t bb[4];
                ldsm4(bb, vb_ld + i * 64);
                mma16816(d0, a[2 * i], bb[0], bb[1]);
                mma16816(d1, a[2 * i + 1], bb[2], bb[3]);
            }
#pragma unroll
            for (int i = 0; i < 4; i++) d0[i] += d1[i];
            float v0, v1;
            fold_hilo(d0, t, v0, v1);
            st_rlx(dst, nzf(v0));
            st_rlx(dst + 128, nzf(v1));
        }
        TSIF(tid == 0, 32);
        {
            const float* src = &S.e4[h][0][tid >> 6][2 * (tid & 63)];
            uint32_t vb2_st = sb + OFF_VB2 + (tid >> 6) * 272 + (tid & 63) * 4;
            uint2 v[4];
#pragma unroll
            for (int i = 0; i < 4; i++) v[i] = ld_rlx2(src + i * 512);
            pin(vb2_st);
            bool have = false;
            int it = 0;
            while (true) {
                if (!have && mbar_test(bar + 8 * BAR_WO) && mbar_test(bar + 8 * (BAR_WO + 1)) && mbar_test(bar + 8 * (BAR_WO + 2)) &&
                    mbar_test(bar + 8 * (BAR_WO + 3))) {
                    have = true;
#pragma unroll
                    for (int ks = 0; ks < 8; ks++) ldsm4t(ao[ks], awo + ks * 16 * 304);
                }
                bool ok = true;
#pragma unroll
                for (int i = 0; i < 4; i++)
                    if (!full2(v[i])) { ok = false; v[i] = ld_rlx2(src + i * 512); }
                if (__all_sync(0xffffffffu, ok)) break;
                if (++it > SPIN_LIMIT) __trap();
            }
            const float y0 = (__uint_as_float(v[0].x) + __uint_as_float(v[1].x)) + (__uint_as_float(v[2].x) + __uint_as_float(v[3].x));
            const float y1 = (__uint_as_float(v[0].y) + __uint_as_float(v[1].y)) + (__uint_as_float(v[2].y) + __uint_as_float(v[3].y));
            const uint32_t hi = pack_bf16(y0, y1);
            const uint32_t lo = pack_bf16(y0 - bf_lo(hi), y1 - bf_hi(hi));
            sts32(vb2_st, hi);
            sts32(vb2_st + 4 * 272, lo);
            have_o = have;
        }
        TSIF(tid == 0, 33);
    }

    if (warp < 9) {
        if (!have_o) {
#pragma unroll
            for (int ks = 0; ks < 8; ks++) {
                if ((ks & 1) == 0) mbar_wait(bar + 8 * (BAR_WO + (ks >> 1)));
                ldsm4t(ao[ks], awo + ks * 16 * 304);
            }
        }
        const int b0 = 2 * (t & 1), row = g + 8 * (t >> 1);
        uint32_t am = sb + OFF_MLP + (b0 * 144 + 16 * warp + row) * 4, ag = sb + OFF_GATE + b0 * 4;
        uint32_t vb2_ld = sb + OFF_VB2 + lr * 272 + li * 16;
        float* dst = &S.e5[2 * (9 * j + warp) + (t & 1)][h][row * 2];
        pin(am); pin(ag); pin(vb2_ld); pin(dst);
        nb_sync(NB_O, 384);
        TSIF(tid == 0, 34);
        float d0[4] = {0.f, 0.f, 0.f, 0.f}, d1[4] = {0.f, 0.f, 0.f, 0.f};
#pragma unroll
        for (int i = 0; i < 4; i++) {
            uint32_t bb[4];
            ldsm4(bb, vb2_ld + i * 64);
            mma16816(d0, ao[2 * i], bb[0], bb[1]);
            mma16816(d1, ao[2 * i + 1], bb[2], bb[3]);
        }
        const float g0 = ldsf(ag), g1 = ldsf(ag + 4);
        const float m0 = ldsf(am), m1 = ldsf(am + 144 * 4);
#pragma unroll
        for (int i = 0; i < 4; i++) d0[i] += d1[i];
        float v0, v1;
        fold_hilo(d0, t, v0, v1);
        st_rlx2(dst, nzf(fmaf(g0, v0, m0)), nzf(fmaf(g1, v1, m1)));
        TSIF(tid == 0, 35);
    } else {
        nb_sync(NB_O, 384);
        if (cta < 72) {
            const uint4* src = reinterpret_cast<const uint4*>(&S.e5[cta][li][lr * 4]);
            uint4 v[8];
#pragma unroll
            for (int i = 0; i < 8; i++) v[i] = ld_rlx4(src + i * 32);
            int it = 0;
            while (true) {
                bool ok = true;
#pragma unroll
                for (int i = 0; i < 8; i++)
                    if (!full4(v[i])) { ok = false; v[i] = ld_rlx4(src + i * 32); }
                if (ok) break;
                if (++it > SPIN_LIMIT) __trap();
            }
            __syncwarp();
            TSIF(lane == 0, 36);
            float c0 = 0.f, c1 = 0.f, c2 = 0.f, c3 = 0.f;
#pragma unroll
            for (int i = 0; i < 8; i++) {
                c0 += __uint_as_float(v[i].x); c1 += __uint_as_float(v[i].y);
                c2 += __uint_as_float(v[i].z); c3 += __uint_as_float(v[i].w);
            }
            const bool u16 = lane & 16, u8 = lane & 8;
            const float r0 = (u16 ? c2 : c0) + __shfl_xor_sync(0xffffffffu, u16 ? c0 : c2, 16);
            const float r1 = (u16 ? c3 : c1) + __shfl_xor_sync(0xffffffffu, u16 ? c1 : c3, 16);
            const float y = (u8 ? r1 : r0) + __shfl_xor_sync(0xffffffffu, u8 ? r0 : r1, 8);
            out[(2 * (cta & 1) + (u8 ? 1 : 0)) * DM + 16 * (cta >> 1) + 2 * lr + (u16 ? 1 : 0)] = __float2bfloat16(y);
            TSIF(lane == 0, 37);
        }
    }
    TS_END();
}

typedef CUresult (*EncodeTiledFn)(CUtensorMap*, CUtensorMapDataType, cuuint32_t, void*, const cuuint64_t*, const cuuint64_t*,
                                  const cuuint32_t*, const cuuint32_t*, CUtensorMapInterleave, CUtensorMapSwizzle,
                                  CUtensorMapL2promotion, CUtensorMapFloatOOBfill);

static void encode_map(EncodeTiledFn enc, CUtensorMap* m, const void* p, uint64_t rows, uint64_t cols, uint64_t group_cols,
                       uint32_t box_cols, uint32_t box_rows, CUtensorMapSwizzle swz) {
    cuuint64_t dims[3] = {group_cols, rows, cols / group_cols};
    cuuint64_t strides[2] = {cols * 2, group_cols * 2};
    cuuint32_t box[3] = {box_cols, box_rows, 1};
    cuuint32_t es[3] = {1, 1, 1};
    enc(m, CU_TENSOR_MAP_DATA_TYPE_BFLOAT16, 3, const_cast<void*>(p), dims, strides, box, es, CU_TENSOR_MAP_INTERLEAVE_NONE,
        swz, CU_TENSOR_MAP_L2_PROMOTION_L2_128B, CU_TENSOR_MAP_FLOAT_OOB_FILL_NONE);
}

}

extern "C" void kernel_launch(void* const* d_in, const int* in_sizes, int n_in, void* d_out, int out_size) {
    using namespace gm;
    (void)in_sizes; (void)n_in; (void)out_size;
    static EncodeTiledFn enc = nullptr;
    if (!enc) {
        void* fn = nullptr;
        cudaDriverEntryPointQueryResult q;
        cudaGetDriverEntryPoint("cuTensorMapEncodeTiled", &fn, cudaEnableDefault, &q);
        enc = (EncodeTiledFn)fn;
        cudaFuncSetAttribute(gated_mix_kernel, cudaFuncAttributeMaxDynamicSharedMemorySize, SMEM_BYTES);
    }
    Maps maps;
    encode_map(enc, &maps.wq, d_in[2], 576, 4096, 64, 64, 72, CU_TENSOR_MAP_SWIZZLE_128B);
    encode_map(enc, &maps.wuk, d_in[3], 512, 4096, 64, 64, 64, CU_TENSOR_MAP_SWIZZLE_128B);
    encode_map(enc, &maps.ckv, d_in[1], 16384, 512, 64, 64, 64, CU_TENSOR_MAP_SWIZZLE_128B);
    encode_map(enc, &maps.wuv, d_in[4], 512, 4096, 64, 64, 64, CU_TENSOR_MAP_SWIZZLE_128B);
    encode_map(enc, &maps.wo, d_in[5], 4096, 576, 576, 152, 32, CU_TENSOR_MAP_SWIZZLE_NONE);
    gated_mix_kernel<<<NCTA, NTHREADS, SMEM_BYTES>>>(
        maps, (const __nv_bfloat16*)d_in[0], (const __nv_bfloat16*)d_in[7], (const __nv_bfloat16*)d_in[8],
        (const __nv_bfloat16*)d_in[9], (const __nv_bfloat16*)d_in[10], (const __nv_bfloat16*)d_in[11],
        (__nv_bfloat16*)d_out);
}
```

```cpp
#include <cuda_runtime.h>
#include <cuda_bf16.h>
#include <cuda.h>
#include <stdint.h>

namespace gm {

constexpr int DM = 576;
constexpr int NCTA = 128;
constexpr int NTHREADS = 480;
constexpr int SPIN_LIMIT = 1 << 20;
#define GM_T0 0
#define GM_DT 330
#define GM_W 6
#define GM_K2 24
#define GM_DT2 290
#define GM_HOLD 2
#define GM_HOLDAT 0
#define GM_E3GATE 1
#define GM_E2DELAY 900
#define GM_CLRGAP 40
#define GM_CLRAT 3
#define GM_MLPN 72
#define GM_MLP1 40
#define GM_MLP2 50
#define GM_S3AT 1
#define GM_SUSPEND 20000
#define GM_QSLEEP 100
#define GM_CLRDELAY 0
#define GM_E4DELAY 250
#define GM_E5DELAY 150

constexpr uint32_t OFF_C = 0;
constexpr uint32_t OFF_A = 131072;
constexpr uint32_t OFF_X0 = OFF_A + 16384;
constexpr uint32_t OFF_B = OFF_A + 36864;
constexpr uint32_t OFF_P = OFF_B + 32768;
constexpr uint32_t OFF_X2 = OFF_P + 8192;
constexpr uint32_t OFF_VB = OFF_X2 + 8192;
constexpr uint32_t OFF_VB2 = OFF_VB + 2176;
constexpr uint32_t OFF_WMAX = OFF_VB2 + 2176;
constexpr uint32_t OFF_WSUM = OFF_WMAX + 2048;
constexpr uint32_t OFF_MLP = OFF_WSUM + 1024;
constexpr uint32_t OFF_COEF = OFF_MLP + 2304;
constexpr uint32_t OFF_GATE = OFF_COEF + 2336;
constexpr uint32_t OFF_X = OFF_X2;
constexpr uint32_t OFF_GW = OFF_X + 4608;
constexpr uint32_t OFF_W1 = OFF_GW + 1152;
constexpr uint32_t OFF_RED = OFF_WMAX;
constexpr uint32_t OFF_BAR = OFF_GATE + 16;
constexpr uint32_t SMEM_USED = OFF_BAR + 46 * 8;
constexpr uint32_t SMEM_BYTES = SMEM_USED + 1024 + 512;
static_assert(SMEM_BYTES <= 232448, "shared memory");

enum { BAR_WQ = 0, BAR_WUK = 4, BAR_C = 8, BAR_WUV = 24, BAR_WO = 28, BAR_X = 32, BAR_BFREE = 36, BAR_CFREE = 37, BAR_GO = 38, BAR_QGATE = 39, BAR_IN = 40, BAR_XQ = 41, BAR_QREADY = 42, BAR_QW = 43, BAR_PVDONE = 44, BAR_PREAD = 45 };
enum { NB_INIT = 0, NB_MAIN = 1, NB_MLP = 2, NB_O = 3, NB_SUM = 4, NB_Q = 6, NB_S0 = 7 };

struct Scratch {
    uint32_t qabs[2][4][8][32][32];
    uint32_t part[32][4][4][16][64];
    float2 ml[32][4][16];
    float e4[32][4][4][128];
    float e5[72][32][32];
};

__device__ __align__(1024) Scratch g_scratch;
__device__ __align__(128) unsigned int g_count[2][32];

#define TS(i)
#define TSIF(c, i)
#define CK32(var, dep)
#define CKST(c, i, v)
#define TS_END()

struct Maps { CUtensorMap wq, wuk, ckv, wuv, wo; };

__device__ __forceinline__ uint32_t smem_u32(const void* p) { return (uint32_t)__cvta_generic_to_shared(p); }
__device__ __forceinline__ void mbar_init(uint32_t bar, int cnt) {
    asm volatile("mbarrier.init.shared::cta.b64 [%0], %1;" ::"r"(bar), "r"(cnt) : "memory");
}
__device__ __forceinline__ void mbar_expect(uint32_t bar, uint32_t bytes) {
    asm volatile("mbarrier.arrive.expect_tx.shared::cta.b64 _, [%0], %1;" ::"r"(bar), "r"(bytes) : "memory");
}
__device__ __forceinline__ void mbar_arrive(uint32_t bar) {
    asm volatile("mbarrier.arrive.shared::cta.b64 _, [%0];" ::"r"(bar) : "memory");
}
__device__ __forceinline__ void mbar_wait(uint32_t bar) {
    uint32_t ok;
    int it = 0;
    do {
        asm volatile("{ .reg .pred p; mbarrier.try_wait.parity.shared::cta.b64 p, [%1], 0, %2; selp.u32 %0, 1, 0, p; }"
                     : "=r"(ok) : "r"(bar), "n"(GM_SUSPEND) : "memory");
        if (++it > SPIN_LIMIT) __trap();
    } while (!ok);
}
__device__ __forceinline__ uint32_t map_peer(uint32_t addr, uint32_t rank) {
    uint32_t r; asm("mapa.shared::cluster.u32 %0, %1, %2;" : "=r"(r) : "r"(addr), "r"(rank)); return r;
}
__device__ __forceinline__ void st_async4(uint32_t addr, float a, float b, float c, float d, uint32_t bar) {
    asm volatile("st.async.weak.shared::cluster.mbarrier::complete_tx::bytes.v4.f32 [%0], {%1,%2,%3,%4}, [%5];"
                 ::"r"(addr), "f"(a), "f"(b), "f"(c), "f"(d), "r"(bar) : "memory");
}
__device__ __forceinline__ void mbar_spin(uint32_t bar) {
    uint32_t ok;
    int it = 0;
    do {
        asm volatile("{ .reg .pred p; mbarrier.try_wait.parity.shared::cta.b64 p, [%1], 0; selp.u32 %0, 1, 0, p; }"
                     : "=r"(ok) : "r"(bar) : "memory");
        if (++it > SPIN_LIMIT) __trap();
    } while (!ok);
}
__device__ __forceinline__ uint32_t now_ns() { uint32_t t; asm volatile("mov.u32 %0, %%globaltimer_lo;" : "=r"(t)); return t; }
__device__ __forceinline__ void spin_clk(uint32_t n) {
    uint32_t t0, t;
    asm volatile("mov.u32 %0, %%clock;" : "=r"(t0));
    do { asm volatile("mov.u32 %0, %%clock;" : "=r"(t)); } while (t - t0 < n);
}
__device__ __forceinline__ bool mbar_test(uint32_t bar) {
    uint32_t ok;
    asm volatile("{ .reg .pred p; mbarrier.test_wait.parity.shared::cta.b64 p, [%1], 0; selp.u32 %0, 1, 0, p; }"
                 : "=r"(ok) : "r"(bar) : "memory");
    return ok;
}
__device__ __forceinline__ bool elect_one() {
    uint32_t r;
    asm volatile("{ .reg .pred p; elect.sync _|p, 0xffffffff; selp.u32 %0, 1, 0, p; }" : "=r"(r));
    return r;
}
__device__ __forceinline__ bool nb_sync_any(int id, int n, bool v) {
    uint32_t r;
    asm volatile("{ .reg .pred p, q; setp.ne.u32 p, %3, 0; bar.red.or.pred q, %1, %2, p; selp.u32 %0, 1, 0, q; }"
                 : "=r"(r) : "r"(id), "r"(n), "r"((uint32_t)v) : "memory");
    return r;
}
__device__ __forceinline__ void st_async2(uint32_t addr, float a, float b, uint32_t bar) {
    asm volatile("st.async.weak.shared::cluster.mbarrier::complete_tx::bytes.v2.f32 [%0], {%1,%2}, [%3];"
                 ::"r"(addr), "f"(a), "f"(b), "r"(bar) : "memory");
}
__device__ __forceinline__ void cluster_arrive() { asm volatile("barrier.cluster.arrive.relaxed.aligned;" ::: "memory"); }
__device__ __forceinline__ void cluster_wait() { asm volatile("barrier.cluster.wait.acquire.aligned;" ::: "memory"); }
__device__ __forceinline__ void st_zero4(void* p) {
    asm volatile("st.relaxed.gpu.global.v4.u32 [%0], {%1,%1,%1,%1};" ::"l"(p), "r"(0u) : "memory");
}
__device__ __forceinline__ void nb_sync(int id, int n) { asm volatile("bar.sync %0, %1;" ::"r"(id), "r"(n) : "memory"); }
__device__ __forceinline__ void nb_arrive(int id, int n) { asm volatile("bar.arrive %0, %1;" ::"r"(id), "r"(n) : "memory"); }
__device__ __forceinline__ void fence_async_smem() { asm volatile("fence.proxy.async.shared::cta;" ::: "memory"); }

__device__ __forceinline__ void tma3d(uint32_t dst, const CUtensorMap* m, int c0, int c1, int c2, uint32_t bar, uint64_t pol) {
    asm volatile("cp.async.bulk.tensor.3d.shared::cluster.global.mbarrier::complete_tx::bytes.L2::cache_hint"
                 " [%0], [%1, {%3, %4, %5}], [%2], %6;"
                 ::"r"(dst), "l"(m), "r"(bar), "r"(c0), "r"(c1), "r"(c2), "l"(pol) : "memory");
}

__device__ __forceinline__ void bulk_load(uint32_t dst, const void* src, uint32_t bytes, uint32_t bar) {
    asm volatile("cp.async.bulk.shared::cluster.global.mbarrier::complete_tx::bytes [%0], [%1], %2, [%3];"
                 ::"r"(dst), "l"(src), "r"(bytes), "r"(bar) : "memory");
}
__device__ __forceinline__ void sts128(uint32_t a, const uint4& v) {
    asm volatile("st.shared.v4.u32 [%0], {%1,%2,%3,%4};" ::"r"(a), "r"(v.x), "r"(v.y), "r"(v.z), "r"(v.w) : "memory");
}
__device__ __forceinline__ uint32_t lds32(uint32_t a) { uint32_t v; asm volatile("ld.shared.u32 %0, [%1];" : "=r"(v) : "r"(a) : "memory"); return v; }
__device__ __forceinline__ float lds_bf16(uint32_t a) {
    unsigned short v; asm volatile("ld.shared.u16 %0, [%1];" : "=h"(v) : "r"(a) : "memory"); return __uint_as_float((uint32_t)v << 16);
}
__device__ __forceinline__ void ldsm4(uint32_t (&r)[4], uint32_t a) {
    asm volatile("ldmatrix.sync.aligned.m8n8.x4.shared.b16 {%0,%1,%2,%3}, [%4];"
                 : "=r"(r[0]), "=r"(r[1]), "=r"(r[2]), "=r"(r[3]) : "r"(a) : "memory");
}
__device__ __forceinline__ void ldsm4t(uint32_t (&r)[4], uint32_t a) {
    asm volatile("ldmatrix.sync.aligned.m8n8.x4.trans.shared.b16 {%0,%1,%2,%3}, [%4];"
                 : "=r"(r[0]), "=r"(r[1]), "=r"(r[2]), "=r"(r[3]) : "r"(a) : "memory");
}
__device__ __forceinline__ void stsm4t(uint32_t a, uint32_t r0, uint32_t r1, uint32_t r2, uint32_t r3) {
    asm volatile("stmatrix.sync.aligned.m8n8.x4.trans.shared.b16 [%0], {%1,%2,%3,%4};"
                 ::"r"(a), "r"(r0), "r"(r1), "r"(r2), "r"(r3) : "memory");
}
__device__ __forceinline__ void mma16816(float (&d)[4], const uint32_t (&a)[4], uint32_t b0, uint32_t b1) {
    asm volatile("mma.sync.aligned.m16n8k16.row.col.f32.bf16.bf16.f32 {%0,%1,%2,%3}, {%4,%5,%6,%7}, {%8,%9}, {%0,%1,%2,%3};"
                 : "+f"(d[0]), "+f"(d[1]), "+f"(d[2]), "+f"(d[3])
                 : "r"(a[0]), "r"(a[1]), "r"(a[2]), "r"(a[3]), "r"(b0), "r"(b1));
}

__device__ __forceinline__ void tensor_warmup() {
    float d[4] = {0.f, 0.f, 0.f, 0.f};
    const uint32_t a[4] = {0u, 0u, 0u, 0u};
    mma16816(d, a, 0u, 0u);
    asm volatile("" ::"f"(d[0]));
}
__device__ __forceinline__ uint32_t gdesc(uint32_t addr) { return ((addr & 0x3FFFF) >> 4) | (1u << 16); }
__device__ __forceinline__ void wg_fence() { asm volatile("wgmma.fence.sync.aligned;" ::: "memory"); }
__device__ __forceinline__ void wg_commit() { asm volatile("wgmma.commit_group.sync.aligned;" ::: "memory"); }
template <int N> __device__ __forceinline__ void wg_wait() { asm volatile("wgmma.wait_group.sync.aligned %0;" ::"n"(N) : "memory"); }
template <int TA>
__device__ __forceinline__ void wgmma32(float (&d)[16], uint32_t da, uint32_t db) {
    asm volatile("{\n.reg .b64 da, db;\nmov.b64 da, {%16, 0x40000040};\nmov.b64 db, {%17, 0x40000040};\n"
                 "wgmma.mma_async.sync.aligned.m64n32k16.f32.bf16.bf16 "
                 "{%0,%1,%2,%3,%4,%5,%6,%7,%8,%9,%10,%11,%12,%13,%14,%15}, da, db, 1, 1, 1, %18, 0;\n}"
                 : "+f"(d[0]), "+f"(d[1]), "+f"(d[2]), "+f"(d[3]), "+f"(d[4]), "+f"(d[5]), "+f"(d[6]), "+f"(d[7]),
                   "+f"(d[8]), "+f"(d[9]), "+f"(d[10]), "+f"(d[11]), "+f"(d[12]), "+f"(d[13]), "+f"(d[14]), "+f"(d[15])
                 : "r"(da), "r"(db), "n"(TA));
}
__device__ __forceinline__ void reg_fence(float (&d)[16]) {
#pragma unroll
    for (int i = 0; i < 16; i++) asm volatile("" : "+f"(d[i])::"memory");
}

__device__ __forceinline__ uint32_t ld_rlx(const void* p) {
    uint32_t v; asm volatile("ld.relaxed.gpu.global.u32 %0, [%1];" : "=r"(v) : "l"(p) : "memory"); return v;
}
__device__ __forceinline__ uint2 ld_rlx2(const void* p) {
    uint2 v; asm volatile("ld.relaxed.gpu.global.v2.u32 {%0,%1}, [%2];" : "=r"(v.x), "=r"(v.y) : "l"(p) : "memory"); return v;
}
__device__ __forceinline__ uint4 ld_rlx4(const void* p) {
    uint4 v; asm volatile("ld.relaxed.gpu.global.v4.u32 {%0,%1,%2,%3}, [%4];" : "=r"(v.x), "=r"(v.y), "=r"(v.z), "=r"(v.w) : "l"(p) : "memory"); return v;
}
__device__ __forceinline__ void st_rlx(void* p, uint32_t v) { asm volatile("st.relaxed.gpu.global.u32 [%0], %1;" ::"l"(p), "r"(v) : "memory"); }
__device__ __forceinline__ void st_rlx2(void* p, uint32_t a, uint32_t b) {
    asm volatile("st.relaxed.gpu.global.v2.u32 [%0], {%1,%2};" ::"l"(p), "r"(a), "r"(b) : "memory");
}
__device__ __forceinline__ uint32_t nz(uint32_t v) { return v == 0u ? 0x80000000u : v; }
__device__ __forceinline__ uint32_t nzf(float v) { return nz(__float_as_uint(v)); }
__device__ __forceinline__ bool full2(const uint2& v) { return v.x != 0u && v.y != 0u; }
__device__ __forceinline__ bool full4(const uint4& v) { return v.x != 0u && v.y != 0u && v.z != 0u && v.w != 0u; }

__device__ __forceinline__ uint32_t pack_bf16(float lo, float hi) {
    uint32_t r; asm("cvt.rn.bf16x2.f32 %0, %1, %2;" : "=r"(r) : "f"(hi), "f"(lo)); return r;
}
__device__ __forceinline__ float bf_lo(uint32_t v) { return __uint_as_float(v << 16); }
__device__ __forceinline__ float bf_hi(uint32_t v) { return __uint_as_float(v & 0xFFFF0000u); }
__device__ __forceinline__ float ex2(float x) { float r; asm("ex2.approx.ftz.f32 %0, %1;" : "=f"(r) : "f"(x)); return r; }
__device__ __forceinline__ float tanh_fast(float x) { float r; asm("tanh.approx.f32 %0, %1;" : "=f"(r) : "f"(x)); return r; }
__device__ __forceinline__ void sts32(uint32_t a, uint32_t v) { asm volatile("st.shared.u32 [%0], %1;" ::"r"(a), "r"(v) : "memory"); }
__device__ __forceinline__ void sts16(uint32_t a, uint32_t v) { asm volatile("st.shared.u16 [%0], %1;" ::"r"(a), "h"((unsigned short)v) : "memory"); }
__device__ __forceinline__ void stsf(uint32_t a, float v) { asm volatile("st.shared.f32 [%0], %1;" ::"r"(a), "f"(v) : "memory"); }
__device__ __forceinline__ float ldsf(uint32_t a) { float v; asm volatile("ld.shared.f32 %0, [%1];" : "=f"(v) : "r"(a) : "memory"); return v; }
__device__ __forceinline__ float2 ldsf2(uint32_t a) {
    float2 v; asm volatile("ld.shared.v2.f32 {%0,%1}, [%2];" : "=f"(v.x), "=f"(v.y) : "r"(a) : "memory"); return v;
}
__device__ __forceinline__ float4 ldsf4(uint32_t a) {
    float4 v; asm volatile("ld.shared.v4.f32 {%0,%1,%2,%3}, [%4];" : "=f"(v.x), "=f"(v.y), "=f"(v.z), "=f"(v.w) : "r"(a) : "memory"); return v;
}
__device__ __forceinline__ float max4(const float4& v) { return fmaxf(fmaxf(v.x, v.y), fmaxf(v.z, v.w)); }
__device__ __forceinline__ float sum4(const float4& v) { return (v.x + v.y) + (v.z + v.w); }

template <bool IS_MAX>
__device__ __forceinline__ float reduce_heads(float (&v)[8], int lane) {
    auto op = [](float a, float b) { return IS_MAX ? fmaxf(a, b) : a + b; };
    const bool up16 = lane & 16, up8 = lane & 8, up4 = lane & 4;
    float a[4], b[2];
#pragma unroll
    for (int i = 0; i < 4; i++) {
        float send = up16 ? v[i] : v[i + 4], keep = up16 ? v[i + 4] : v[i];
        a[i] = op(keep, __shfl_xor_sync(0xffffffffu, send, 16));
    }
#pragma unroll
    for (int i = 0; i < 2; i++) {
        float send = up8 ? a[i] : a[i + 2], keep = up8 ? a[i + 2] : a[i];
        b[i] = op(keep, __shfl_xor_sync(0xffffffffu, send, 8));
    }
    float send = up4 ? b[0] : b[1], keep = up4 ? b[1] : b[0];
    return op(keep, __shfl_xor_sync(0xffffffffu, send, 4));
}

__device__ __forceinline__ void fold_hilo(const float (&d)[4], int t, float& v0, float& v1) {
    const bool up = t & 2;
    float s0 = up ? d[0] : d[2], s1 = up ? d[1] : d[3];
    float k0 = up ? d[2] : d[0], k1 = up ? d[3] : d[1];
    v0 = k0 + __shfl_xor_sync(0xffffffffu, s0, 2);
    v1 = k1 + __shfl_xor_sync(0xffffffffu, s1, 2);
}

template <typename T> __device__ __forceinline__ void pin(T*& p) { asm volatile("" : "+l"(p)); }
__device__ __forceinline__ void pin(uint32_t& v) { asm volatile("" : "+r"(v)); }

struct Attn {
    uint32_t sb, xloc, xrem, xbar, wmax_st, wmax_ld, p_st, wsum, dpv;
    int wg, wp, lane;
    float acc[2][16], mref[8], ls[8], s[16];
    uint32_t pk[8];

    __device__ __forceinline__ void setup(uint32_t sb_, int rank, int wg_, int wp_, int lane_) {
        sb = sb_; wg = wg_; wp = wp_; lane = lane_;
        const int g = lane >> 2, t = lane & 3, myhead = 8 * (g >> 1) + 2 * t + (g & 1);
        xloc = sb + (wp * 32 + lane) * 16;
        xrem = map_peer(xloc, rank ^ 1);
        xbar = map_peer(sb + OFF_BAR + 8 * BAR_X, rank ^ 1);
        wmax_st = sb + OFF_WMAX + myhead * 16 + wp * 4;
        wmax_ld = sb + OFF_WMAX + t * 32;
        p_st = sb + OFF_P + wg * 4096 + (8 * (lane >> 4) + (lane & 7)) * 128 + (((2 * wp + ((lane >> 3) & 1)) ^ (lane & 7)) << 4);
        wsum = sb + OFF_WSUM + myhead * 32;
        dpv = gdesc(sb + OFF_C) + wg * 1024;
        pin(xloc); pin(xrem); pin(xbar); pin(wmax_st); pin(wmax_ld); pin(p_st); pin(wsum); pin(dpv);
#pragma unroll
        for (int i = 0; i < 16; i++) acc[0][i] = acc[1][i] = s[i] = 0.f;
#pragma unroll
        for (int i = 0; i < 8; i++) mref[i] = ls[i] = 0.f;
        reg_fence(acc[0]); reg_fence(acc[1]); reg_fence(s);
    }
    static __device__ __forceinline__ uint32_t xoff(int tile) { return tile == 2 ? OFF_X2 : OFF_X0 + (tile == 1 ? 8192u : 0u); }

    template <int TILE> __device__ __forceinline__ void scores_issue() {
        const uint32_t bar = sb + OFF_BAR + 8 * (BAR_C + TILE * 4);
        const uint32_t dc = gdesc(sb + OFF_C + TILE * 32768), dq = gdesc(sb + OFF_A);
        if (TILE == 1) nb_sync(NB_S0, 256);
        TSIF(lane == 0 && wp == 0 && TILE == 0, 52);
        const bool all = mbar_test(bar + 24) && mbar_test(bar + 16) && mbar_test(bar + 8) && mbar_test(bar);
        if (TILE >= 2) {
#pragma unroll
            for (int i = 0; i < 16; i++) s[i] = 0.f;
        }
        reg_fence(s);
        TSIF(lane == 0 && wp == 0 && TILE == 0, 53);
#pragma unroll
        for (int q = 0; q < 4; q++) {
            if (!all) mbar_spin(bar + 8 * q);
            wg_fence();
#pragma unroll
            for (int k = 0; k < 4; k++) wgmma32<0>(s, dc + q * 512 + k * 2, dq + q * 256 + k * 2);
            wg_commit();
        }
        if (TILE == 0) nb_arrive(NB_S0, 256);
        TSIF(lane == 0 && wp == 0 && TILE == 0, 54);
        wg_wait<0>();
        reg_fence(s);
        reg_fence(acc[0]);
        reg_fence(acc[1]);
#pragma unroll
        for (int i = 0; i < 4; i++) st_async4(xrem + xoff(TILE) + i * 2048, s[4 * i], s[4 * i + 1], s[4 * i + 2], s[4 * i + 3], xbar + 8 * TILE);
        TSIF(lane == 0 && wp == 0, 16 + TILE);
    }
    __device__ __forceinline__ void write_p() {
#pragma unroll
        for (int jj = 0; jj < 4; jj++) {
            pk[2 * jj] = pack_bf16(ex2(s[4 * jj]), ex2(s[4 * jj + 1]));
            pk[2 * jj + 1] = pack_bf16(ex2(s[4 * jj + 2]), ex2(s[4 * jj + 3]));
        }
        stsm4t(p_st, pk[0], pk[1], pk[2], pk[3]);
        stsm4t(p_st + 2048, pk[4], pk[5], pk[6], pk[7]);
        fence_async_smem();
    }
    __device__ __forceinline__ void exact(int st, bool mine) {
        if (mine) {
            float mx[8];
#pragma unroll
            for (int i = 0; i < 4; i++) {
                mx[2 * i] = fmaxf(s[4 * i], s[4 * i + 2]);
                mx[2 * i + 1] = fmaxf(s[4 * i + 1], s[4 * i + 3]);
            }
            stsf(wmax_st + (st & 1) * 512, reduce_heads<true>(mx, lane));
        }
        nb_sync(NB_MAIN, 256);
#pragma unroll
        for (int i = 0; i < 8; i++) {
            float d = max4(ldsf4(wmax_ld + (st & 1) * 512 + (8 * (i >> 1) + (i & 1)) * 16));
            const int r = 4 * (i >> 1) + (i & 1);
            if (st > 0) {
                d = fmaxf(d, 0.f);
                const float al = ex2(-d);
                ls[i] *= al;
                acc[0][r] *= al; acc[0][r + 2] *= al; acc[1][r] *= al; acc[1][r + 2] *= al;
            }
            mref[i] += d;
            if (mine) { s[r] -= d; s[r + 2] -= d; }
        }
        if (mine) write_p();
        reg_fence(acc[0]);
        reg_fence(acc[1]);
        nb_sync(NB_MAIN, 256);
    }
    __device__ __forceinline__ void publish_sum() { stsf(wsum + (4 * wg + wp) * 4, reduce_heads<false>(ls, lane)); }
    __device__ __forceinline__ void stage(int st) {
        const bool mine = wg == (st & 1);
        bool bad = false;
        if (mine) {
#pragma unroll
            for (int i = 0; i < 16; i++) s[i] -= mref[2 * (i >> 2) + (i & 1)];
            const uint32_t xa = xloc + xoff(st);
            mbar_spin(sb + OFF_BAR + 8 * (BAR_X + st));
#pragma unroll
            for (int i = 0; i < 4; i++) {
                const float4 r = ldsf4(xa + i * 2048);
                s[4 * i] += r.x; s[4 * i + 1] += r.y; s[4 * i + 2] += r.z; s[4 * i + 3] += r.w;
            }
            TSIF(lane == 0 && wp == 0, 20 + st);
            write_p();
            const uint32_t hi = __vimax3_u16x2(__vimax3_u16x2(pk[0], pk[1], pk[2]), __vimax3_u16x2(pk[3], pk[4], pk[5]), __vmaxu2(pk[6], pk[7]));
            const uint32_t lo = __vimin3_u16x2(__vimin3_u16x2(pk[0], pk[1], pk[2]), __vimin3_u16x2(pk[3], pk[4], pk[5]), __vminu2(pk[6], pk[7]));
            bad = max(hi >> 16, hi & 0xFFFFu) > 0x4F80u || (st == 0 && min(lo >> 16, lo & 0xFFFFu) < 0x2F80u);
        } else if (st == 3) {
            publish_sum();
        }
        const uint32_t dp = gdesc(sb + OFF_P) + (st & 1) * 256, da = dpv + st * 2048;
        wg_wait<0>();
        reg_fence(acc[0]);
        reg_fence(acc[1]);
        if (st == 2 && lane == 0) mbar_arrive(sb + OFF_BAR + 8 * BAR_CFREE);
        if (nb_sync_any(NB_MAIN, 256, bad)) {
            exact(st, mine);
            if (st == 3 && !mine) publish_sum();
        }
        wg_fence();
#pragma unroll
        for (int T = 0; T < 2; T++)
#pragma unroll
            for (int k = 0; k < 4; k++) wgmma32<1>(acc[T], da + T * 512 + k * 128, dp + k * 2);
        wg_commit();
        if (mine) {
#pragma unroll
            for (int jj = 0; jj < 4; jj++) {
                ls[2 * jj] += bf_lo(pk[2 * jj]) + bf_lo(pk[2 * jj + 1]);
                ls[2 * jj + 1] += bf_hi(pk[2 * jj]) + bf_hi(pk[2 * jj + 1]);
            }
        }
        if (st == 3) {
            if (mine) {
                publish_sum();
                if (wp == 0 && lane < 4) {
                    sts128(sb + OFF_WMAX + 1536 + lane * 32, make_uint4(__float_as_uint(mref[0]), __float_as_uint(mref[1]), __float_as_uint(mref[2]), __float_as_uint(mref[3])));
                    sts128(sb + OFF_WMAX + 1536 + lane * 32 + 16, make_uint4(__float_as_uint(mref[4]), __float_as_uint(mref[5]), __float_as_uint(mref[6]), __float_as_uint(mref[7])));
                }
            }
            nb_arrive(NB_SUM, 288);
        }
    }
    __device__ __forceinline__ void run() {
        if (wg == 0) scores_issue<0>(); else scores_issue<1>();
#pragma unroll 1
        for (int st = 0; st < 4; st++) {
            stage(st);
            if (wg == 0 && st == 0) {
                scores_issue<2>();
            } else if (wg == 1 && st == GM_S3AT) {
                scores_issue<3>();
            }
            TSIF(lane == 0 && wp == 0 && wg == 0, 24 + st);
        }
        wg_wait<0>();
        reg_fence(acc[0]);
        reg_fence(acc[1]);
    }
};

__global__ void __cluster_dims__(2, 1, 1) __launch_bounds__(NTHREADS, 1)
gated_mix_kernel(const __grid_constant__ Maps maps, const __nv_bfloat16* __restrict__ x,
                 const __nv_bfloat16* __restrict__ w1, const __nv_bfloat16* __restrict__ b1,
                 const __nv_bfloat16* __restrict__ w2, const __nv_bfloat16* __restrict__ b2,
                 const __nv_bfloat16* __restrict__ gate_w, __nv_bfloat16* __restrict__ out) {
    extern __shared__ __align__(1024) unsigned char smem_raw[];
    const uint32_t sb = (smem_u32(smem_raw) + 1023u) & ~1023u;
    const uint32_t bar = sb + OFF_BAR;
    const int tid = threadIdx.x, lane = tid & 31;
    const int warp = __shfl_sync(0xffffffffu, tid >> 5, 0);
    const int cta = blockIdx.x, h = cta >> 2, j = cta & 3;
    const int rank = cta & 1, bq = cta >> 5, split = (cta >> 1) & 15;
    const int g = lane >> 2, t = lane & 3, lr = lane & 7, li = lane >> 3;
    Scratch& S = g_scratch;
    uint32_t ao[8][4];
    bool have_o = false;
    const uint32_t awo = sb + OFF_C + (lr + 8 * (li >> 1)) * 304 + (2 * warp + (li & 1)) * 16;

    if (warp == 12) {
        const uint32_t t_start = now_ns();
        uint64_t pol;
        asm volatile("createpolicy.fractional.L2::evict_first.b64 %0, 1.0;" : "=l"(pol));
        const bool leader = elect_one();
        if (leader) {
            TS(0);
#pragma unroll
            for (int i = 0; i < 4; i++) mbar_init(bar + 8 * i, 1);
            asm volatile("fence.mbarrier_init.release.cluster;" ::: "memory");
#pragma unroll
            for (int q = 0; q < 4; q++) {
                mbar_expect(bar + 8 * q, 9216);
                tma3d(sb + OFF_A + q * 9216, &maps.wq, 0, rank * 288 + q * 72, j >> 1 | h << 1, bar + 8 * q, pol);
                TSIF(q == 0, 1);
            }
        }
        __syncwarp();
        nb_sync(NB_INIT, NTHREADS);
        cluster_arrive();
        if (leader) {
            auto pace = [&](int i) {
                const uint32_t due = GM_T0 + i * GM_DT - max(i - GM_K2, 0) * (GM_DT - GM_DT2);
                if (i >= GM_W) mbar_spin(bar + 8 * (i - GM_W));
                int it = 0;
                while (now_ns() - t_start < due && ++it < SPIN_LIMIT) {}
            };
#pragma unroll 1
            for (int q = 0; q < 4; q++) {
                const int i = BAR_WUK + q;
                pace(i);
                mbar_expect(bar + 8 * i, 8192);
                tma3d(sb + OFF_B + q * 8192, &maps.wuk, 0, rank * 256 + q * 64, j >> 1 | h << 1, bar + 8 * i, pol);
            }
#pragma unroll 1
            for (int q = 0; q < 16; q++) {
                const int i = BAR_C + q;
                pace(i);
                mbar_expect(bar + 8 * i, 8192);
                tma3d(sb + OFF_C + q * 8192, &maps.ckv, 0, (cta >> 1) * 256 + (q >> 2) * 64, 4 * rank + (q & 3), bar + 8 * i, pol);
            }
            mbar_spin(bar + 8 * BAR_BFREE);
#pragma unroll 1
            for (int q = 0; q < 4; q++) {
                const int i = BAR_WUV + q;
                pace(i);
                mbar_expect(bar + 8 * i, 8192);
                tma3d(sb + OFF_B + (q & 1) * 16384 + (q >> 1) * 8192, &maps.wuv, 0, j * 128 + (q >> 1) * 64, 2 * h + (q & 1), bar + 8 * i, pol);
            }
            mbar_spin(bar + 8 * BAR_CFREE);
#pragma unroll 1
            for (int q = 0; q < 4; q++) {
                const int i = BAR_WO + q;
                if (q == 4 - GM_HOLD) mbar_spin(bar + 8 * BAR_PREAD);
                pace(i);
                mbar_expect(bar + 8 * i, 9728);
                tma3d(sb + OFF_C + q * 9728, &maps.wo, j * 144, h * 128 + q * 32, 0, bar + 8 * i, pol);
            }
        }
        TS_END();
        return;
    }
    if (warp >= 13) {
        const bool leader = elect_one();
        if (leader && warp == 13) {
            mbar_init(bar + 8 * BAR_IN, 1);
            asm volatile("fence.mbarrier_init.release.cluster;" ::: "memory");
            mbar_expect(bar + 8 * BAR_IN, 4608 + 1152 + 864);
            bulk_load(sb + OFF_X, x, 4608, bar + 8 * BAR_IN);
            bulk_load(sb + OFF_GW, gate_w, 1152, bar + 8 * BAR_IN);
            bulk_load(sb + OFF_W1, w1 + h * 144, 288, bar + 8 * BAR_IN);
            bulk_load(sb + OFF_W1 + 288, b1 + h * 144, 288, bar + 8 * BAR_IN);
            bulk_load(sb + OFF_W1 + 576, w2 + h * 144, 288, bar + 8 * BAR_IN);
            mbar_init(bar + 8 * BAR_XQ, 1);
            mbar_init(bar + 8 * BAR_QW, 8);
            mbar_init(bar + 8 * BAR_PVDONE, 8);
            mbar_init(bar + 8 * BAR_PREAD, 1);
            asm volatile("fence.mbarrier_init.release.cluster;" ::: "memory");
            mbar_expect(bar + 8 * BAR_XQ, 2048);
        }
        __syncwarp();
        if (warp == 13) {
#pragma unroll
            for (int i = 0; i < 4; i++) st_zero4(&S.qabs[j >> 1][i][4 * rank + li][h][lr * 4]);
        }
        nb_sync(NB_INIT, NTHREADS);
        cluster_arrive();
        auto arrive = [&](unsigned* ctr, int ts) {
            unsigned old = 0;
            __syncwarp();
            if (leader) {
                asm volatile("atom.add.release.gpu.global.u32 %0, [%1], 1;" : "=r"(old) : "l"(ctr) : "memory");
                TS(ts);
            }
            __syncwarp();
            return (old & ~(unsigned)(NCTA - 1)) + NCTA;
        };
        auto wait_all = [&](const unsigned* ctr, unsigned target, int go, int ts) {
            if (leader) {
                int it = 0;
                while (true) {
                    unsigned v;
                    asm volatile("ld.acquire.gpu.global.u32 %0, [%1];" : "=r"(v) : "l"(ctr) : "memory");
                    if ((int)(v - target) >= 0) break;
                    if (++it > SPIN_LIMIT) __trap();
                    __nanosleep(GM_QSLEEP);
                }
                mbar_arrive(bar + 8 * go);
                TS(ts);
            }
            __syncwarp();
        };
        auto clear_late = [&]() {
            char* pp = reinterpret_cast<char*>(&S.part[0][2 * rank + li / 2][bq][split][(lane & 15) * 4]);
#pragma unroll 1
            for (int i = 0; i < 32; i++) {
                st_zero4(pp + i * sizeof(S.part[0]));
                spin_clk(GM_CLRGAP);
            }
#pragma unroll
            for (int i = 0; i < 4; i++) st_zero4(&S.e4[h][j][i][lane * 4]);
#pragma unroll
            for (int i = 0; i < 5; i++)
                if (4 * i + li < 18) st_zero4(&S.e5[18 * j + 4 * i + li][h][lr * 4]);
            if (lane < 8) st_zero4(reinterpret_cast<uint4*>(&S.ml[0][0][0]) + cta * 8 + lane);
            TSIF(lane == 0, 10);
        };
        if (warp == 13) {
            wait_all(&g_count[0][0], arrive(&g_count[0][0], 9), BAR_QGATE, 11);
            TS_END();
            return;
        }
        if (GM_CLRAT >= 0) mbar_wait(bar + 8 * GM_CLRAT);
        clear_late();
        wait_all(&g_count[1][0], arrive(&g_count[1][0], 4), BAR_GO, 5);
        {
            float2* dst = &S.ml[lane][bq][split];
            pin(dst);
            mbar_wait(bar + 8 * BAR_GO);
            nb_sync(NB_SUM, 288);
            const float l = sum4(ldsf4(sb + OFF_WSUM + lane * 32)) + sum4(ldsf4(sb + OFF_WSUM + lane * 32 + 16));
            const float m = ldsf(sb + OFF_WMAX + 1536 + ((lane >> 1) & 3) * 32 + (2 * (lane >> 3) + (lane & 1)) * 4);
            if (rank == 0) st_rlx2(dst, nzf(m), nzf(l));
        }
        TS_END();
        return;
    }

    if (warp >= 8) {
        const int b = warp - 8, mt = tid - 256;
        uint32_t xv[9], gv[9];
        float hv[9], acc[9];
        const float bias2 = (h == 0 && lane < 16) ? __bfloat162float(b2[0]) : 0.f;
        nb_sync(NB_INIT, NTHREADS);
        cluster_arrive();
        mbar_wait(bar + 8 * BAR_IN);
#pragma unroll
        for (int k = 0; k < 9; k++) {
            xv[k] = lds32(sb + OFF_X + b * (DM * 2) + (lane + 32 * k) * 4);
            gv[k] = lds32(sb + OFF_GW + (lane + 32 * k) * 4);
            hv[k] = lds_bf16(sb + OFF_X + (b * DM + j * 144 + (lane & 15) + 16 * k) * 2);
        }
#pragma unroll
        for (int i = 0; i < 2; i++) {
            const int f = mt + 128 * i;
            if (f < 144) {
                const float cw = lds_bf16(sb + OFF_W1 + f * 2), cb = lds_bf16(sb + OFF_W1 + 288 + f * 2), cv = lds_bf16(sb + OFF_W1 + 576 + f * 2);
                sts128(sb + OFF_COEF + f * 16, make_uint4(__float_as_uint(cw), __float_as_uint(cb), __float_as_uint(0.5f * cv), 0u));
            }
        }
        float sum = 0.f, z = 0.f;
#pragma unroll
        for (int k = 0; k < 9; k++) {
            sum += bf_lo(xv[k]) + bf_hi(xv[k]);
            z = fmaf(bf_lo(xv[k]), bf_lo(gv[k]), fmaf(bf_hi(xv[k]), bf_hi(gv[k]), z));
        }
#pragma unroll
        for (int o = 16; o; o >>= 1) {
            sum += __shfl_xor_sync(0xffffffffu, sum, o);
            z += __shfl_xor_sync(0xffffffffu, z, o);
        }
        const float mean = sum * (1.f / DM);
        float var = 0.f;
#pragma unroll
        for (int k = 0; k < 9; k++) {
            const float d0 = bf_lo(xv[k]) - mean, d1 = bf_hi(xv[k]) - mean;
            var = fmaf(d0, d0, fmaf(d1, d1, var));
        }
#pragma unroll
        for (int o = 16; o; o >>= 1) var += __shfl_xor_sync(0xffffffffu, var, o);
        const float rstd = rsqrtf(var * (1.f / DM) + 1e-5f);
        const float gate = __fdividef(1.f, 1.f + __expf(-z));
        if (lane == 0) stsf(sb + OFF_GATE + b * 4, gate);
#pragma unroll
        for (int k = 0; k < 9; k++) { hv[k] = (hv[k] - mean) * rstd; acc[k] = 0.f; }
        nb_arrive(NB_Q, 384);
        nb_sync(NB_MLP, 128);
        TSIF(mt == 0, 3);
        float p0 = 0.f, p1 = bias2;
        const uint32_t ca = sb + OFF_COEF + (lane >> 4) * 72 * 16;
        constexpr float K0 = 0.7978845608028654f, K1 = 0.7978845608028654f * 0.044715f;
        float u[9], u2[9], tt[9], in[9], hu[9], th[9];
        float4 c = ldsf4(ca), cn = ldsf4(ca + 16);
#pragma unroll
        for (int q = 0; q < 9; q++) th[q] = hu[q] = 0.f;
#pragma unroll
        for (int q = 0; q < 4; q++) { u[q] = fmaf(hv[q], c.x, c.y); u2[q] = u[q] * u[q]; tt[q] = fmaf(u2[q], K1, K0); }
        in[0] = u[0] * tt[0];
        hu[0] = u[0] * c.z;
        int f = 0;
#pragma unroll 1
        for (int seg = 0; seg < 3; seg++) {
            const int fend = seg == 0 ? GM_MLP1 : seg == 1 ? GM_MLP2 : GM_MLPN;
            if (seg > 0) {
                TSIF(mt == 0, 46 + 2 * seg);
                mbar_wait(bar + 8 * (seg == 1 ? BAR_QW : BAR_PVDONE));
                TSIF(mt == 0, 47 + 2 * seg);
            }
#pragma unroll 2
            for (; f < fend; f++) {
                const float4 cnn = ldsf4(ca + (f + 2) * 16);
                p0 = fmaf(c.x, c.z, p0);
                p1 = fmaf(c.y, c.z, p1);
#pragma unroll
                for (int q = 0; q < 9; q++) {
                    const int q1 = (q + 1) % 9, q2 = (q + 2) % 9, q3 = (q + 3) % 9, q4 = (q + 4) % 9, qm = (q + 6) % 9;
                    asm volatile("fma.rn.f32 %0, %1, %2, %0;" : "+f"(acc[qm]) : "f"(hu[qm]), "f"(th[qm]));
                    asm volatile("tanh.approx.f32 %0, %1;" : "=f"(th[q]) : "f"(in[q]));
                    asm volatile("fma.rn.f32 %0, %1, %2, %3;" : "=f"(u[q4]) : "f"(hv[q4]), "f"(q + 4 >= 9 ? cn.x : c.x), "f"(q + 4 >= 9 ? cn.y : c.y));
                    asm volatile("mul.rn.f32 %0, %1, %1;" : "=f"(u2[q3]) : "f"(u[q3]));
                    asm volatile("fma.rn.f32 %0, %1, %2, %3;" : "=f"(tt[q2]) : "f"(u2[q2]), "f"(K1), "f"(K0));
                    asm volatile("mul.rn.f32 %0, %1, %2;" : "=f"(in[q1]) : "f"(u[q1]), "f"(tt[q1]));
                    asm volatile("mul.rn.f32 %0, %1, %2;" : "=f"(hu[q1]) : "f"(u[q1]), "f"(q + 1 >= 9 ? cn.z : c.z));
                }
                c = cn;
                cn = cnn;
            }
        }
#pragma unroll
        for (int q = 6; q < 9; q++) acc[q] = fmaf(hu[q], th[q], acc[q]);
        const float og = 1.f - gate;
#pragma unroll
        for (int k = 0; k < 9; k++) {
            float v = acc[k] + fmaf(hv[k], p0, p1);
            v += __shfl_xor_sync(0xffffffffu, v, 16);
            if (lane < 16) stsf(sb + OFF_MLP + (b * 144 + lane + 16 * k) * 4, og * v);
        }
        TSIF(mt == 0, 8);
        if (warp >= 9) {
            nb_arrive(NB_O, 384);
            TS_END();
            return;
        }
    } else {
        const int wg = warp >> 2, wp = warp & 3;
        if (elect_one()) {
#pragma unroll
            for (int i = 0; i < 4; i++) mbar_init(bar + 8 * (4 + 4 * warp + i), 1);
            if (warp == 7) {
#pragma unroll
                for (int i = 0; i < 4; i++) mbar_expect(bar + 8 * (BAR_X + i), 8192);
            }
            if (warp < 4) mbar_init(bar + 8 * (BAR_BFREE + warp), warp < 2 ? 8 : 1);
            asm volatile("fence.mbarrier_init.release.cluster;" ::: "memory");
        }
        __syncwarp();
        nb_sync(NB_INIT, NTHREADS);
        cluster_arrive();

        {
            uint32_t xb[9][2];
            mbar_wait(bar + 8 * BAR_IN);
#pragma unroll
            for (int ks = 0; ks < 9; ks++) {
                const uint32_t px = sb + OFF_X + ((g & 3) * DM + rank * 288 + wg * 144 + ks * 16) * 2 + t * 4;
                xb[ks][0] = g < 4 ? lds32(px) : 0u;
                xb[ks][1] = g < 4 ? lds32(px + 16) : 0u;
            }
            float d[4] = {0.f, 0.f, 0.f, 0.f};
            const uint32_t a0 = sb + OFF_A + (wg * 144 + lr + 8 * (li >> 1)) * 128 + (((2 * wp + (li & 1)) ^ lr) << 4);
            const uint32_t ql = sb + OFF_P + (2 * rank + wg) * 1024 + (16 * wp + g) * 16 + (t & 1) * 8;
            const uint32_t qr = map_peer(ql, rank ^ 1), qb = map_peer(bar + 8 * BAR_XQ, rank ^ 1);
            cluster_wait();
            mbar_wait(bar + 8 * (BAR_WQ + 2 * wg));
            mbar_wait(bar + 8 * (BAR_WQ + 2 * wg + 1));
#pragma unroll
            for (int ks = 0; ks < 9; ks++) {
                uint32_t a[4];
                ldsm4t(a, a0 + ks * 2048);
                mma16816(d, a, xb[ks][0], xb[ks][1]);
            }
            if (t < 2) {
                st_async2(qr, d[0], d[1], qb);
                st_async2(qr + 128, d[2], d[3], qb);
                asm volatile("st.shared.v2.f32 [%0], {%1,%2};" ::"r"(ql), "f"(d[0]), "f"(d[1]) : "memory");
                asm volatile("st.shared.v2.f32 [%0], {%1,%2};" ::"r"(ql + 128), "f"(d[2]), "f"(d[3]) : "memory");
            }
            nb_sync(NB_MAIN, 256);
            TSIF(tid == 0, 12);
            if (tid < 128) {
                mbar_wait(bar + 8 * BAR_XQ);
                const uint32_t qa = sb + OFF_P + tid * 8;
                const float2 v0 = ldsf2(qa), v1 = ldsf2(qa + 1024), v2 = ldsf2(qa + 2048), v3 = ldsf2(qa + 3072);
                const float q0 = (v0.x + v1.x) + (v2.x + v3.x), q1 = (v0.y + v1.y) + (v2.y + v3.y);
                const uint32_t hi = pack_bf16(q0, q1);
                const uint32_t lo = pack_bf16(q0 - bf_lo(hi), q1 - bf_hi(hi));
                const uint32_t a = sb + OFF_VB + (2 * (tid & 1)) * 272 + (tid >> 1) * 2;
                sts16(a, hi & 0xFFFFu);
                sts16(a + 272, hi >> 16);
                sts16(a + 4 * 272, lo & 0xFFFFu);
                sts16(a + 5 * 272, lo >> 16);
            }
        }
        TSIF(tid == 0, 13);
        {
            uint32_t a[2][4][4];
            const uint32_t a0 = sb + OFF_B + (32 * warp + lr + 8 * (li & 1)) * 128;
            const bool odd = g & 1;
            const int cl = 32 * warp + (g & ~1) + 8 * (t >> 1);
            uint32_t* dst = &S.qabs[j >> 1][2 * (t & 1) + (odd ? 1 : 0)][4 * rank + (cl >> 6)][h][(cl & 7) >> 1];
            const int ch = (cl & 63) >> 3;
            mbar_wait(bar + 8 * (BAR_WUK + (warp >> 1)));
#pragma unroll
            for (int mt = 0; mt < 2; mt++)
#pragma unroll
                for (int ks = 0; ks < 4; ks++) ldsm4(a[mt][ks], a0 + mt * 2048 + (((2 * ks + (li >> 1)) ^ lr) << 4));
            nb_sync(NB_Q, 384);
            uint32_t bb[2][4];
            ldsm4(bb[0], sb + OFF_VB + lr * 272 + li * 16);
            ldsm4(bb[1], sb + OFF_VB + lr * 272 + li * 16 + 64);
            if (lane == 0) mbar_arrive(bar + 8 * BAR_BFREE);
#pragma unroll
            for (int mt = 0; mt < 2; mt++) {
                float d[4] = {0.f, 0.f, 0.f, 0.f};
#pragma unroll
                for (int ks = 0; ks < 4; ks++) mma16816(d, a[mt][ks], bb[ks >> 1][2 * (ks & 1)], bb[ks >> 1][2 * (ks & 1) + 1]);
                float v0, v1;
                fold_hilo(d, t, v0, v1);
                const float sc = 0.08838834764831845f * 1.4426950408889634f;
                v0 *= sc; v1 *= sc;
                const float got = __shfl_xor_sync(0xffffffffu, odd ? v0 : v1, 4);
                const uint32_t w = odd ? pack_bf16(got, v1) : pack_bf16(v0, got);
                st_rlx(dst + (((ch + 2 * mt) ^ (h & 7)) << 2), nz(w));
            }
            __syncwarp();
            if (lane == 0) mbar_arrive(bar + 8 * BAR_QW);
        }
        TSIF(tid == 0, 14);
        uint32_t* part_st = &S.part[2 * t][2 * rank + wg][bq][split][wp * 16 + g * 2];
        const uint4* part_ld = reinterpret_cast<const uint4*>(&S.part[h][j][warp >> 1][li][(warp & 1) * 32 + lr * 4]);
        const float2* ml_ld = &S.ml[h][warp >> 1][lane & 15];
        pin(part_st); pin(part_ld); pin(ml_ld);

        Attn at;
        {
            const uint4* src = reinterpret_cast<const uint4*>(&S.qabs[0][bq][4 * rank][0][0]) + tid;
            constexpr int HALF = sizeof(S.qabs[0]) / 16;
            pin(src);
            at.setup(sb, rank, wg, wp, lane);
            mbar_spin(bar + 8 * BAR_QGATE);
            spin_clk(GM_E2DELAY);
            TSIF(tid == 0, 2);
            uint4 v[8];
#pragma unroll
            for (int i = 0; i < 8; i++) v[i] = ld_rlx4(src + (i >> 2) * HALF + (i & 3) * 256);
            tensor_warmup();
            int it = 0;
            while (true) {
                bool ok = true;
#pragma unroll
                for (int i = 0; i < 8; i++)
                    if (!full4(v[i])) { ok = false; v[i] = ld_rlx4(src + (i >> 2) * HALF + (i & 3) * 256); }
                if (ok) break;
                if (++it > SPIN_LIMIT) __trap();
            }
            TSIF(tid == 0, 55);
            auto add2 = [](uint32_t x, uint32_t y) { uint32_t r; asm("add.rn.bf16x2 %0, %1, %2;" : "=r"(r) : "r"(x), "r"(y)); return r; };
#pragma unroll
            for (int i = 0; i < 4; i++)
                asm volatile("st.shared.v4.u32 [%0], {%1,%2,%3,%4};" ::"r"(sb + OFF_A + (tid + 256 * i) * 16),
                             "r"(add2(v[i].x, v[i + 4].x)), "r"(add2(v[i].y, v[i + 4].y)), "r"(add2(v[i].z, v[i + 4].z)), "r"(add2(v[i].w, v[i + 4].w)) : "memory");
            fence_async_smem();
            nb_sync(NB_MAIN, 256);
        }
        TSIF(tid == 0, 15);

        at.run();
        mbar_wait(bar + 8 * BAR_GO);

        TSIF(tid == 0, 27);
#pragma unroll
        for (int i = 0; i < 8; i++) {
            const int r = 4 * (i >> 1) + (i & 1);
            st_rlx2(part_st + (8 * (i >> 1) + (i & 1)) * (4 * 4 * 16 * 64),
                    nz(pack_bf16(at.acc[0][r], at.acc[0][r + 2])), nz(pack_bf16(at.acc[1][r], at.acc[1][r + 2])));
        }
        TSIF(tid == 0, 28);
        if (lane == 0) mbar_arrive(bar + 8 * BAR_PVDONE);
        if (GM_HOLDAT == 2 && tid == 0) mbar_arrive(bar + 8 * BAR_PREAD);

        uint32_t a[8][4];
        {
            const uint32_t auv = sb + OFF_B + wg * 16384 + (lr + 8 * (li >> 1)) * 128 + (((2 * wp + (li & 1)) ^ lr) << 4);
            uint2 mlv = ld_rlx2(ml_ld);
            uint4 v[4];
            if (!GM_E3GATE) {
#pragma unroll
                for (int i = 0; i < 4; i++) v[i] = ld_rlx4(part_ld + i * 64);
            }
            int it = 0;
            if (GM_HOLDAT == 3 && tid == 0 && mlv.x != 0x12345u) mbar_arrive(bar + 8 * BAR_PREAD);
            while (!__all_sync(0xffffffffu, full2(mlv))) {
                mlv = ld_rlx2(ml_ld);
                if (++it > SPIN_LIMIT) __trap();
            }
            if (GM_E3GATE) {
#pragma unroll
                for (int i = 0; i < 4; i++) v[i] = ld_rlx4(part_ld + i * 64);
            }
            if (GM_HOLDAT == 0 && tid == 0) mbar_arrive(bar + 8 * BAR_PREAD);
            const float m = __uint_as_float(mlv.x);
            float M = m;
#pragma unroll
            for (int o = 8; o; o >>= 1) M = fmaxf(M, __shfl_xor_sync(0xffffffffu, M, o));
            const float e = ex2(m - M);
            float L = e * __uint_as_float(mlv.y);
#pragma unroll
            for (int o = 8; o; o >>= 1) L += __shfl_xor_sync(0xffffffffu, L, o);
            const float wgt = __fdividef(e, L);
            float w[4];
#pragma unroll
            for (int i = 0; i < 4; i++) w[i] = __shfl_sync(0xffffffffu, wgt, 4 * i + li);
            const int b = warp >> 1, half = warp & 1;
            const bool u16 = lane & 16, u8 = lane & 8;
            uint32_t vb_st = sb + OFF_VB + b * 272 + ((u16 ? 64 : 0) + 16 * (2 * half + (lr >> 2)) + (u8 ? 8 : 0) + 2 * (lr & 3)) * 2;
            pin(vb_st);
            TSIF(tid == 0, 29);
            bool have = false;
            it = 0;
            while (true) {
                if (!have && mbar_test(bar + 8 * (BAR_WUV + wg)) && mbar_test(bar + 8 * (BAR_WUV + 2 + wg))) {
                    have = true;
#pragma unroll
                    for (int ks = 0; ks < 8; ks++) ldsm4t(a[ks], auv + ks * 2048);
                }
                bool ok = true;
#pragma unroll
                for (int i = 0; i < 4; i++)
                    if (!full4(v[i])) { ok = false; v[i] = ld_rlx4(part_ld + i * 64); }
                if (__all_sync(0xffffffffu, ok)) break;
                if (++it > SPIN_LIMIT) __trap();
            }
            TSIF(tid == 0, 30);
            if (GM_HOLDAT == 1 && tid == 0) mbar_arrive(bar + 8 * BAR_PREAD);
            float c[8];
#pragma unroll
            for (int i = 0; i < 8; i++) c[i] = 0.f;
#pragma unroll
            for (int i = 0; i < 4; i++) {
                c[0] = fmaf(w[i], bf_lo(v[i].x), c[0]); c[1] = fmaf(w[i], bf_hi(v[i].x), c[1]);
                c[2] = fmaf(w[i], bf_lo(v[i].y), c[2]); c[3] = fmaf(w[i], bf_hi(v[i].y), c[3]);
                c[4] = fmaf(w[i], bf_lo(v[i].z), c[4]); c[5] = fmaf(w[i], bf_hi(v[i].z), c[5]);
                c[6] = fmaf(w[i], bf_lo(v[i].w), c[6]); c[7] = fmaf(w[i], bf_hi(v[i].w), c[7]);
            }
            float r0 = (u16 ? c[2] : c[0]) + __shfl_xor_sync(0xffffffffu, u16 ? c[0] : c[2], 16);
            float r1 = (u16 ? c[3] : c[1]) + __shfl_xor_sync(0xffffffffu, u16 ? c[1] : c[3], 16);
            float r2 = (u16 ? c[6] : c[4]) + __shfl_xor_sync(0xffffffffu, u16 ? c[4] : c[6], 16);
            float r3 = (u16 ? c[7] : c[5]) + __shfl_xor_sync(0xffffffffu, u16 ? c[5] : c[7], 16);
            const float y0 = (u8 ? r1 : r0) + __shfl_xor_sync(0xffffffffu, u8 ? r0 : r1, 8);
            const float y1 = (u8 ? r3 : r2) + __shfl_xor_sync(0xffffffffu, u8 ? r2 : r3, 8);
            const uint32_t hi = pack_bf16(y0, y1);
            const uint32_t lo = pack_bf16(y0 - bf_lo(hi), y1 - bf_hi(hi));
            sts32(vb_st, hi);
            sts32(vb_st + 4 * 272, lo);
            if (!have) {
                mbar_wait(bar + 8 * (BAR_WUV + wg));
                mbar_wait(bar + 8 * (BAR_WUV + 2 + wg));
#pragma unroll
                for (int ks = 0; ks < 8; ks++) ldsm4t(a[ks], auv + ks * 2048);
            }
        }
        {
            float* dst = &S.e4[h][j][2 * (t & 1)][16 * warp + g + 8 * (t >> 1)];
            uint32_t vb_ld = sb + OFF_VB + lr * 272 + li * 16;
            pin(dst); pin(vb_ld);
            nb_sync(NB_MAIN, 256);
            TSIF(tid == 0, 31);
            float d0[4] = {0.f, 0.f, 0.f, 0.f}, d1[4] = {0.f, 0.f, 0.f, 0.f};
#pragma unroll
            for (int i = 0; i < 4; i++) {
                uint32_t bb[4];
                ldsm4(bb, vb_ld + i * 64);
                mma16816(d0, a[2 * i], bb[0], bb[1]);
                mma16816(d1, a[2 * i + 1], bb[2], bb[3]);
            }
#pragma unroll
            for (int i = 0; i < 4; i++) d0[i] += d1[i];
            float v0, v1;
            fold_hilo(d0, t, v0, v1);
            st_rlx(dst, nzf(v0));
            st_rlx(dst + 128, nzf(v1));
        }
        TSIF(tid == 0, 32);
        {
            const float* src = &S.e4[h][0][tid >> 6][2 * (tid & 63)];
            uint32_t vb2_st = sb + OFF_VB2 + (tid >> 6) * 272 + (tid & 63) * 4;
            uint2 v[4];
            spin_clk(GM_E4DELAY);
#pragma unroll
            for (int i = 0; i < 4; i++) v[i] = ld_rlx2(src + i * 512);
            pin(vb2_st);
            bool have = false;
            int it = 0;
            while (true) {
                if (!have && mbar_test(bar + 8 * BAR_WO) && mbar_test(bar + 8 * (BAR_WO + 1)) && mbar_test(bar + 8 * (BAR_WO + 2)) &&
                    mbar_test(bar + 8 * (BAR_WO + 3))) {
                    have = true;
#pragma unroll
                    for (int ks = 0; ks < 8; ks++) ldsm4t(ao[ks], awo + ks * 16 * 304);
                }
                if (__all_sync(0xffffffffu, full2(v[0]) && full2(v[1]) && full2(v[2]) && full2(v[3]))) break;
#pragma unroll
                for (int i = 0; i < 4; i++) v[i] = ld_rlx2(src + i * 512);
                if (++it > SPIN_LIMIT) __trap();
            }
            const float y0 = (__uint_as_float(v[0].x) + __uint_as_float(v[1].x)) + (__uint_as_float(v[2].x) + __uint_as_float(v[3].x));
            const float y1 = (__uint_as_float(v[0].y) + __uint_as_float(v[1].y)) + (__uint_as_float(v[2].y) + __uint_as_float(v[3].y));
            const uint32_t hi = pack_bf16(y0, y1);
            const uint32_t lo = pack_bf16(y0 - bf_lo(hi), y1 - bf_hi(hi));
            sts32(vb2_st, hi);
            sts32(vb2_st + 4 * 272, lo);
            have_o = have;
        }
        TSIF(tid == 0, 33);
    }

    {
        if (!have_o) {
#pragma unroll
            for (int ks = 0; ks < 8; ks++) {
                if ((ks & 1) == 0) mbar_spin(bar + 8 * (BAR_WO + (ks >> 1)));
                ldsm4t(ao[ks], awo + ks * 16 * 304);
            }
        }
        const int b0 = 2 * (t & 1), row = g + 8 * (t >> 1);
        uint32_t am = sb + OFF_MLP + (b0 * 144 + 16 * warp + row) * 4, ag = sb + OFF_GATE + b0 * 4;
        uint32_t vb2_ld = sb + OFF_VB2 + lr * 272 + li * 16;
        float* dst = &S.e5[2 * (9 * j + warp) + (t & 1)][h][row * 2];
        const bool u16 = lane & 16, u8 = lane & 8;
        const uint4* fsrc = reinterpret_cast<const uint4*>(&S.e5[cta < 72 ? cta : 0][(4 * warp + li) & 31][lr * 4]);
        uint32_t red_st = sb + OFF_RED + warp * 128 + (4 * lr + (u16 ? 2 : 0) + (u8 ? 1 : 0)) * 4, red_ld = sb + OFF_RED + lane * 4;
        __nv_bfloat16* odst = out + (2 * (cta & 1) + (lane & 1)) * DM + 16 * (cta >> 1) + (lane >> 1);
        pin(am); pin(ag); pin(vb2_ld); pin(dst); pin(fsrc); pin(red_st); pin(red_ld); pin(odst);
        nb_sync(NB_O, 384);
        TSIF(tid == 0, 34);
        float d0[4] = {0.f, 0.f, 0.f, 0.f}, d1[4] = {0.f, 0.f, 0.f, 0.f};
#pragma unroll
        for (int i = 0; i < 4; i++) {
            uint32_t bb[4];
            ldsm4(bb, vb2_ld + i * 64);
            mma16816(d0, ao[2 * i], bb[0], bb[1]);
            mma16816(d1, ao[2 * i + 1], bb[2], bb[3]);
        }
        const float g0 = ldsf(ag), g1 = ldsf(ag + 4);
        const float m0 = ldsf(am), m1 = ldsf(am + 144 * 4);
#pragma unroll
        for (int i = 0; i < 4; i++) d0[i] += d1[i];
        float v0, v1;
        fold_hilo(d0, t, v0, v1);
        st_rlx2(dst, nzf(fmaf(g0, v0, m0)), nzf(fmaf(g1, v1, m1)));
        TSIF(tid == 0, 35);
        if (cta < 72 && warp < 8) {
            spin_clk(GM_E5DELAY);
            uint4 v;
            int it = 0;
            do {
                v = ld_rlx4(fsrc);
                if (++it > SPIN_LIMIT) __trap();
            } while (!__all_sync(0xffffffffu, full4(v)));
            const float c0 = __uint_as_float(v.x), c1 = __uint_as_float(v.y), c2 = __uint_as_float(v.z), c3 = __uint_as_float(v.w);
            const float r0 = (u16 ? c2 : c0) + __shfl_xor_sync(0xffffffffu, u16 ? c0 : c2, 16);
            const float r1 = (u16 ? c3 : c1) + __shfl_xor_sync(0xffffffffu, u16 ? c1 : c3, 16);
            stsf(red_st, (u8 ? r1 : r0) + __shfl_xor_sync(0xffffffffu, u8 ? r0 : r1, 8));
            if (warp == 0) {
                nb_sync(NB_MAIN, 256);
                TSIF(lane == 0, 36);
                float y[8];
#pragma unroll
                for (int i = 0; i < 8; i++) y[i] = ldsf(red_ld + i * 128);
                *odst = __float2bfloat16(((y[0] + y[1]) + (y[2] + y[3])) + ((y[4] + y[5]) + (y[6] + y[7])));
                TSIF(lane == 0, 37);
            } else {
                nb_arrive(NB_MAIN, 256);
            }
        }
    }
    TS_END();
}

typedef CUresult (*EncodeTiledFn)(CUtensorMap*, CUtensorMapDataType, cuuint32_t, void*, const cuuint64_t*, const cuuint64_t*,
                                  const cuuint32_t*, const cuuint32_t*, CUtensorMapInterleave, CUtensorMapSwizzle,
                                  CUtensorMapL2promotion, CUtensorMapFloatOOBfill);

static void encode_map(EncodeTiledFn enc, CUtensorMap* m, const void* p, uint64_t rows, uint64_t cols, uint64_t group_cols,
                       uint32_t box_cols, uint32_t box_rows, CUtensorMapSwizzle swz) {
    cuuint64_t dims[3] = {group_cols, rows, cols / group_cols};
    cuuint64_t strides[2] = {cols * 2, group_cols * 2};
    cuuint32_t box[3] = {box_cols, box_rows, 1};
    cuuint32_t es[3] = {1, 1, 1};
    enc(m, CU_TENSOR_MAP_DATA_TYPE_BFLOAT16, 3, const_cast<void*>(p), dims, strides, box, es, CU_TENSOR_MAP_INTERLEAVE_NONE,
        swz, CU_TENSOR_MAP_L2_PROMOTION_L2_128B, CU_TENSOR_MAP_FLOAT_OOB_FILL_NONE);
}

}

extern "C" void kernel_launch(void* const* d_in, const int* in_sizes, int n_in, void* d_out, int out_size) {
    using namespace gm;
    (void)in_sizes; (void)n_in; (void)out_size;
    static EncodeTiledFn enc = nullptr;
    if (!enc) {
        void* fn = nullptr;
        cudaDriverEntryPointQueryResult q;
        cudaGetDriverEntryPoint("cuTensorMapEncodeTiled", &fn, cudaEnableDefault, &q);
        enc = (EncodeTiledFn)fn;
        cudaFuncSetAttribute(gated_mix_kernel, cudaFuncAttributeMaxDynamicSharedMemorySize, SMEM_BYTES);
    }
    Maps maps;
    encode_map(enc, &maps.wq, d_in[2], 576, 4096, 64, 64, 72, CU_TENSOR_MAP_SWIZZLE_128B);
    encode_map(enc, &maps.wuk, d_in[3], 512, 4096, 64, 64, 64, CU_TENSOR_MAP_SWIZZLE_128B);
    encode_map(enc, &maps.ckv, d_in[1], 16384, 512, 64, 64, 64, CU_TENSOR_MAP_SWIZZLE_128B);
    encode_map(enc, &maps.wuv, d_in[4], 512, 4096, 64, 64, 64, CU_TENSOR_MAP_SWIZZLE_128B);
    encode_map(enc, &maps.wo, d_in[5], 4096, 576, 576, 152, 32, CU_TENSOR_MAP_SWIZZLE_NONE);
    gated_mix_kernel<<<NCTA, NTHREADS, SMEM_BYTES>>>(
        maps, (const __nv_bfloat16*)d_in[0], (const __nv_bfloat16*)d_in[7], (const __nv_bfloat16*)d_in[8],
        (const __nv_bfloat16*)d_in[9], (const __nv_bfloat16*)d_in[10], (const __nv_bfloat16*)d_in[11],
        (__nv_bfloat16*)d_out);
}
```

```cpp
#include <cuda_runtime.h>
#include <cuda_bf16.h>
#include <cuda.h>
#include <stdint.h>

namespace gm {

constexpr int DM = 576;
constexpr int NCTA = 128;
constexpr int NTHREADS = 480;
constexpr int SPIN_LIMIT = 1 << 20;
#define GM_T0 0
#define GM_DT 330
#define GM_W 7
#define GM_K2 16
#define GM_DT2 310
#define GM_HOLD 2
#define GM_HOLDAT 0
#define GM_E3GATE 1
#define GM_E2DELAY 900
#define GM_CLRGAP 40
#define GM_CLRAT 3
#define GM_THOLD 11500
#define GM_HGAP 0
#define GM_HDEL 300
#define GM_DT3 GM_DT
#define GM_LEAN 1
#define GM_E2GAP 0
#define GM_PROMO CU_TENSOR_MAP_L2_PROMOTION_L2_128B
#define GM_POL 0
#define GM_HINT 0
#define GM_MLPN 72
#define GM_MLP1 40
#define GM_MLP2 50
#define GM_S3AT 1
#define GM_SUSPEND 20000
#define GM_QSLEEP 100
#define GM_CLRDELAY 0
#define GM_E4DELAY 250
#define GM_E5DELAY 150

constexpr uint32_t OFF_C = 0;
constexpr uint32_t OFF_A = 131072;
constexpr uint32_t OFF_X0 = OFF_A + 16384;
constexpr uint32_t OFF_B = OFF_A + 36864;
constexpr uint32_t OFF_P = OFF_B + 32768;
constexpr uint32_t OFF_X2 = OFF_P + 8192;
constexpr uint32_t OFF_VB = OFF_X2 + 8192;
constexpr uint32_t OFF_VB2 = OFF_VB + 2176;
constexpr uint32_t OFF_WMAX = OFF_VB2 + 2176;
constexpr uint32_t OFF_WSUM = OFF_WMAX + 2048;
constexpr uint32_t OFF_MLP = OFF_WSUM + 1024;
constexpr uint32_t OFF_COEF = OFF_MLP + 2304;
constexpr uint32_t OFF_GATE = OFF_COEF + 2336;
constexpr uint32_t OFF_X = OFF_X2;
constexpr uint32_t OFF_GW = OFF_X + 4608;
constexpr uint32_t OFF_W1 = OFF_GW + 1152;
constexpr uint32_t OFF_RED = OFF_WMAX;
constexpr uint32_t OFF_BAR = OFF_GATE + 16;
constexpr uint32_t SMEM_USED = OFF_BAR + 46 * 8;
constexpr uint32_t SMEM_BYTES = SMEM_USED + 1024 + 512;
static_assert(SMEM_BYTES <= 232448, "shared memory");

enum { BAR_WQ = 0, BAR_WUK = 4, BAR_C = 8, BAR_WUV = 24, BAR_WO = 28, BAR_X = 32, BAR_BFREE = 36, BAR_CFREE = 37, BAR_GO = 38, BAR_QGATE = 39, BAR_IN = 40, BAR_XQ = 41, BAR_QREADY = 42, BAR_QW = 43, BAR_PVDONE = 44, BAR_PREAD = 45 };
enum { NB_INIT = 0, NB_MAIN = 1, NB_MLP = 2, NB_O = 3, NB_SUM = 4, NB_Q = 6, NB_S0 = 7 };

struct Scratch {
    uint32_t qabs[2][4][8][32][32];
    uint32_t part[32][4][4][16][64];
    float2 ml[32][4][16];
    float e4[32][4][4][128];
    float e5[72][32][32];
};

__device__ __align__(1024) Scratch g_scratch;
__device__ __align__(128) unsigned int g_count[2][32];

#define TS(i)
#define TSIF(c, i)
#define CK32(var, dep)
#define CKST(c, i, v)
#define TS_END()

struct Maps { CUtensorMap wq, wuk, ckv, wuv, wo; };

__device__ __forceinline__ uint32_t smem_u32(const void* p) { return (uint32_t)__cvta_generic_to_shared(p); }
__device__ __forceinline__ void mbar_init(uint32_t bar, int cnt) {
    asm volatile("mbarrier.init.shared::cta.b64 [%0], %1;" ::"r"(bar), "r"(cnt) : "memory");
}
__device__ __forceinline__ void mbar_expect(uint32_t bar, uint32_t bytes) {
    asm volatile("mbarrier.arrive.expect_tx.shared::cta.b64 _, [%0], %1;" ::"r"(bar), "r"(bytes) : "memory");
}
__device__ __forceinline__ void mbar_arrive(uint32_t bar) {
    asm volatile("mbarrier.arrive.shared::cta.b64 _, [%0];" ::"r"(bar) : "memory");
}
__device__ __forceinline__ void mbar_wait(uint32_t bar) {
    uint32_t ok;
    int it = 0;
    do {
        asm volatile("{ .reg .pred p; mbarrier.try_wait.parity.shared::cta.b64 p, [%1], 0, %2; selp.u32 %0, 1, 0, p; }"
                     : "=r"(ok) : "r"(bar), "n"(GM_SUSPEND) : "memory");
        if (++it > SPIN_LIMIT) __trap();
    } while (!ok);
}
__device__ __forceinline__ uint32_t map_peer(uint32_t addr, uint32_t rank) {
    uint32_t r; asm("mapa.shared::cluster.u32 %0, %1, %2;" : "=r"(r) : "r"(addr), "r"(rank)); return r;
}
__device__ __forceinline__ void st_async4(uint32_t addr, float a, float b, float c, float d, uint32_t bar) {
    asm volatile("st.async.weak.shared::cluster.mbarrier::complete_tx::bytes.v4.f32 [%0], {%1,%2,%3,%4}, [%5];"
                 ::"r"(addr), "f"(a), "f"(b), "f"(c), "f"(d), "r"(bar) : "memory");
}
__device__ __forceinline__ void mbar_arrive_if(uint32_t bar, uint32_t flag) {
    asm volatile("{ .reg .pred p; setp.ne.u32 p, %1, 0; @p mbarrier.arrive.shared::cta.b64 _, [%0]; }" ::"r"(bar), "r"(flag) : "memory");
}
__device__ __forceinline__ void mbar_spin(uint32_t bar) {
    uint32_t ok;
    int it = 0;
    do {
        asm volatile("{ .reg .pred p; mbarrier.try_wait.parity.shared::cta.b64 p, [%1], 0; selp.u32 %0, 1, 0, p; }"
                     : "=r"(ok) : "r"(bar) : "memory");
        if (++it > SPIN_LIMIT) __trap();
    } while (!ok);
}
__device__ __forceinline__ uint32_t now_ns() { uint32_t t; asm volatile("mov.u32 %0, %%globaltimer_lo;" : "=r"(t)); return t; }
__device__ __forceinline__ void spin_clk(uint32_t n) {
    uint32_t t0, t;
    asm volatile("mov.u32 %0, %%clock;" : "=r"(t0));
    do { asm volatile("mov.u32 %0, %%clock;" : "=r"(t)); } while (t - t0 < n);
}
__device__ __forceinline__ bool mbar_test(uint32_t bar) {
    uint32_t ok;
    asm volatile("{ .reg .pred p; mbarrier.test_wait.parity.shared::cta.b64 p, [%1], 0; selp.u32 %0, 1, 0, p; }"
                 : "=r"(ok) : "r"(bar) : "memory");
    return ok;
}
__device__ __forceinline__ bool elect_one() {
    uint32_t r;
    asm volatile("{ .reg .pred p; elect.sync _|p, 0xffffffff; selp.u32 %0, 1, 0, p; }" : "=r"(r));
    return r;
}
__device__ __forceinline__ bool nb_sync_any(int id, int n, bool v) {
    uint32_t r;
    asm volatile("{ .reg .pred p, q; setp.ne.u32 p, %3, 0; bar.red.or.pred q, %1, %2, p; selp.u32 %0, 1, 0, q; }"
                 : "=r"(r) : "r"(id), "r"(n), "r"((uint32_t)v) : "memory");
    return r;
}
__device__ __forceinline__ void st_async2(uint32_t addr, float a, float b, uint32_t bar) {
    asm volatile("st.async.weak.shared::cluster.mbarrier::complete_tx::bytes.v2.f32 [%0], {%1,%2}, [%3];"
                 ::"r"(addr), "f"(a), "f"(b), "r"(bar) : "memory");
}
__device__ __forceinline__ void cluster_arrive() { asm volatile("barrier.cluster.arrive.relaxed.aligned;" ::: "memory"); }
__device__ __forceinline__ void cluster_wait() { asm volatile("barrier.cluster.wait.acquire.aligned;" ::: "memory"); }
__device__ __forceinline__ void st_zero4(void* p) {
    asm volatile("st.relaxed.gpu.global.v4.u32 [%0], {%1,%1,%1,%1};" ::"l"(p), "r"(0u) : "memory");
}
__device__ __forceinline__ void nb_sync(int id, int n) { asm volatile("bar.sync %0, %1;" ::"r"(id), "r"(n) : "memory"); }
__device__ __forceinline__ void nb_arrive(int id, int n) { asm volatile("bar.arrive %0, %1;" ::"r"(id), "r"(n) : "memory"); }
__device__ __forceinline__ void fence_async_smem() { asm volatile("fence.proxy.async.shared::cta;" ::: "memory"); }

__device__ __forceinline__ void tma3d(uint32_t dst, const CUtensorMap* m, int c0, int c1, int c2, uint32_t bar, uint64_t pol) {
    asm volatile("cp.async.bulk.tensor.3d.shared::cluster.global.mbarrier::complete_tx::bytes.L2::cache_hint"
                 " [%0], [%1, {%3, %4, %5}], [%2], %6;"
                 ::"r"(dst), "l"(m), "r"(bar), "r"(c0), "r"(c1), "r"(c2), "l"(pol) : "memory");
}

__device__ __forceinline__ void bulk_load(uint32_t dst, const void* src, uint32_t bytes, uint32_t bar) {
    asm volatile("cp.async.bulk.shared::cluster.global.mbarrier::complete_tx::bytes [%0], [%1], %2, [%3];"
                 ::"r"(dst), "l"(src), "r"(bytes), "r"(bar) : "memory");
}
__device__ __forceinline__ void sts128(uint32_t a, const uint4& v) {
    asm volatile("st.shared.v4.u32 [%0], {%1,%2,%3,%4};" ::"r"(a), "r"(v.x), "r"(v.y), "r"(v.z), "r"(v.w) : "memory");
}
__device__ __forceinline__ uint32_t lds32(uint32_t a) { uint32_t v; asm volatile("ld.shared.u32 %0, [%1];" : "=r"(v) : "r"(a) : "memory"); return v; }
__device__ __forceinline__ float lds_bf16(uint32_t a) {
    unsigned short v; asm volatile("ld.shared.u16 %0, [%1];" : "=h"(v) : "r"(a) : "memory"); return __uint_as_float((uint32_t)v << 16);
}
__device__ __forceinline__ void ldsm4(uint32_t (&r)[4], uint32_t a) {
    asm volatile("ldmatrix.sync.aligned.m8n8.x4.shared.b16 {%0,%1,%2,%3}, [%4];"
                 : "=r"(r[0]), "=r"(r[1]), "=r"(r[2]), "=r"(r[3]) : "r"(a) : "memory");
}
__device__ __forceinline__ void ldsm4t(uint32_t (&r)[4], uint32_t a) {
    asm volatile("ldmatrix.sync.aligned.m8n8.x4.trans.shared.b16 {%0,%1,%2,%3}, [%4];"
                 : "=r"(r[0]), "=r"(r[1]), "=r"(r[2]), "=r"(r[3]) : "r"(a) : "memory");
}
__device__ __forceinline__ void stsm4t(uint32_t a, uint32_t r0, uint32_t r1, uint32_t r2, uint32_t r3) {
    asm volatile("stmatrix.sync.aligned.m8n8.x4.trans.shared.b16 [%0], {%1,%2,%3,%4};"
                 ::"r"(a), "r"(r0), "r"(r1), "r"(r2), "r"(r3) : "memory");
}
__device__ __forceinline__ void mma16816(float (&d)[4], const uint32_t (&a)[4], uint32_t b0, uint32_t b1) {
    asm volatile("mma.sync.aligned.m16n8k16.row.col.f32.bf16.bf16.f32 {%0,%1,%2,%3}, {%4,%5,%6,%7}, {%8,%9}, {%0,%1,%2,%3};"
                 : "+f"(d[0]), "+f"(d[1]), "+f"(d[2]), "+f"(d[3])
                 : "r"(a[0]), "r"(a[1]), "r"(a[2]), "r"(a[3]), "r"(b0), "r"(b1));
}

__device__ __forceinline__ void tensor_warmup() {
    float d[4] = {0.f, 0.f, 0.f, 0.f};
    const uint32_t a[4] = {0u, 0u, 0u, 0u};
    mma16816(d, a, 0u, 0u);
    asm volatile("" ::"f"(d[0]));
}
__device__ __forceinline__ uint32_t gdesc(uint32_t addr) { return ((addr & 0x3FFFF) >> 4) | (1u << 16); }
__device__ __forceinline__ void wg_fence() { asm volatile("wgmma.fence.sync.aligned;" ::: "memory"); }
__device__ __forceinline__ void wg_commit() { asm volatile("wgmma.commit_group.sync.aligned;" ::: "memory"); }
template <int N> __device__ __forceinline__ void wg_wait() { asm volatile("wgmma.wait_group.sync.aligned %0;" ::"n"(N) : "memory"); }
template <int TA>
__device__ __forceinline__ void wgmma32(float (&d)[16], uint32_t da, uint32_t db) {
    asm volatile("{\n.reg .b64 da, db;\nmov.b64 da, {%16, 0x40000040};\nmov.b64 db, {%17, 0x40000040};\n"
                 "wgmma.mma_async.sync.aligned.m64n32k16.f32.bf16.bf16 "
                 "{%0,%1,%2,%3,%4,%5,%6,%7,%8,%9,%10,%11,%12,%13,%14,%15}, da, db, 1, 1, 1, %18, 0;\n}"
                 : "+f"(d[0]), "+f"(d[1]), "+f"(d[2]), "+f"(d[3]), "+f"(d[4]), "+f"(d[5]), "+f"(d[6]), "+f"(d[7]),
                   "+f"(d[8]), "+f"(d[9]), "+f"(d[10]), "+f"(d[11]), "+f"(d[12]), "+f"(d[13]), "+f"(d[14]), "+f"(d[15])
                 : "r"(da), "r"(db), "n"(TA));
}
__device__ __forceinline__ void reg_fence(float (&d)[16]) {
#pragma unroll
    for (int i = 0; i < 16; i++) asm volatile("" : "+f"(d[i])::"memory");
}

__device__ __forceinline__ uint64_t pol_first() { uint64_t p; asm("createpolicy.fractional.L2::evict_first.b64 %0, 1.0;" : "=l"(p)); return p; }
__device__ __forceinline__ uint4 ld_rlx4_ef(const void* p) {
    uint4 v; asm volatile("ld.relaxed.gpu.global.L2::cache_hint.v4.u32 {%0,%1,%2,%3}, [%4], %5;" : "=r"(v.x), "=r"(v.y), "=r"(v.z), "=r"(v.w) : "l"(p), "l"(pol_first()) : "memory"); return v;
}
__device__ __forceinline__ void st_rlx2_ef(void* p, uint32_t a, uint32_t b) {
    asm volatile("st.relaxed.gpu.global.L2::cache_hint.v2.u32 [%0], {%1,%2}, %3;" ::"l"(p), "r"(a), "r"(b), "l"(pol_first()) : "memory");
}
__device__ __forceinline__ uint32_t ld_rlx(const void* p) {
    uint32_t v; asm volatile("ld.relaxed.gpu.global.u32 %0, [%1];" : "=r"(v) : "l"(p) : "memory"); return v;
}
__device__ __forceinline__ uint2 ld_rlx2(const void* p) {
    uint2 v; asm volatile("ld.relaxed.gpu.global.v2.u32 {%0,%1}, [%2];" : "=r"(v.x), "=r"(v.y) : "l"(p) : "memory"); return v;
}
__device__ __forceinline__ uint4 ld_rlx4(const void* p) {
    uint4 v; asm volatile("ld.relaxed.gpu.global.v4.u32 {%0,%1,%2,%3}, [%4];" : "=r"(v.x), "=r"(v.y), "=r"(v.z), "=r"(v.w) : "l"(p) : "memory"); return v;
}
__device__ __forceinline__ void st_rlx(void* p, uint32_t v) { asm volatile("st.relaxed.gpu.global.u32 [%0], %1;" ::"l"(p), "r"(v) : "memory"); }
__device__ __forceinline__ void st_rlx2(void* p, uint32_t a, uint32_t b) {
    asm volatile("st.relaxed.gpu.global.v2.u32 [%0], {%1,%2};" ::"l"(p), "r"(a), "r"(b) : "memory");
}
__device__ __forceinline__ uint32_t nz(uint32_t v) { return max(v, 1u); }
__device__ __forceinline__ uint32_t nzf(float v) { return nz(__float_as_uint(v)); }
__device__ __forceinline__ uint32_t min2(const uint2& v) { return min(v.x, v.y); }
__device__ __forceinline__ uint32_t min4(const uint4& v) { return min(__vimin3_u32(v.x, v.y, v.z), v.w); }
__device__ __forceinline__ bool full2(const uint2& v) { return min2(v) != 0u; }
__device__ __forceinline__ bool full4(const uint4& v) { return min4(v) != 0u; }

__device__ __forceinline__ uint32_t pack_bf16(float lo, float hi) {
    uint32_t r; asm("cvt.rn.bf16x2.f32 %0, %1, %2;" : "=r"(r) : "f"(hi), "f"(lo)); return r;
}
__device__ __forceinline__ float bf_lo(uint32_t v) { return __uint_as_float(v << 16); }
__device__ __forceinline__ float bf_hi(uint32_t v) { return __uint_as_float(v & 0xFFFF0000u); }
__device__ __forceinline__ float ex2(float x) { float r; asm("ex2.approx.ftz.f32 %0, %1;" : "=f"(r) : "f"(x)); return r; }
__device__ __forceinline__ float tanh_fast(float x) { float r; asm("tanh.approx.f32 %0, %1;" : "=f"(r) : "f"(x)); return r; }
__device__ __forceinline__ void sts32(uint32_t a, uint32_t v) { asm volatile("st.shared.u32 [%0], %1;" ::"r"(a), "r"(v) : "memory"); }
__device__ __forceinline__ void sts16(uint32_t a, uint32_t v) { asm volatile("st.shared.u16 [%0], %1;" ::"r"(a), "h"((unsigned short)v) : "memory"); }
__device__ __forceinline__ void stsf(uint32_t a, float v) { asm volatile("st.shared.f32 [%0], %1;" ::"r"(a), "f"(v) : "memory"); }
__device__ __forceinline__ float ldsf(uint32_t a) { float v; asm volatile("ld.shared.f32 %0, [%1];" : "=f"(v) : "r"(a) : "memory"); return v; }
__device__ __forceinline__ float2 ldsf2(uint32_t a) {
    float2 v; asm volatile("ld.shared.v2.f32 {%0,%1}, [%2];" : "=f"(v.x), "=f"(v.y) : "r"(a) : "memory"); return v;
}
__device__ __forceinline__ float4 ldsf4(uint32_t a) {
    float4 v; asm volatile("ld.shared.v4.f32 {%0,%1,%2,%3}, [%4];" : "=f"(v.x), "=f"(v.y), "=f"(v.z), "=f"(v.w) : "r"(a) : "memory"); return v;
}
__device__ __forceinline__ float max4(const float4& v) { return fmaxf(fmaxf(v.x, v.y), fmaxf(v.z, v.w)); }
__device__ __forceinline__ float sum4(const float4& v) { return (v.x + v.y) + (v.z + v.w); }

template <bool IS_MAX>
__device__ __forceinline__ float reduce_heads(float (&v)[8], int lane) {
    auto op = [](float a, float b) { return IS_MAX ? fmaxf(a, b) : a + b; };
    const bool up16 = lane & 16, up8 = lane & 8, up4 = lane & 4;
    float a[4], b[2];
#pragma unroll
    for (int i = 0; i < 4; i++) {
        float send = up16 ? v[i] : v[i + 4], keep = up16 ? v[i + 4] : v[i];
        a[i] = op(keep, __shfl_xor_sync(0xffffffffu, send, 16));
    }
#pragma unroll
    for (int i = 0; i < 2; i++) {
        float send = up8 ? a[i] : a[i + 2], keep = up8 ? a[i + 2] : a[i];
        b[i] = op(keep, __shfl_xor_sync(0xffffffffu, send, 8));
    }
    float send = up4 ? b[0] : b[1], keep = up4 ? b[1] : b[0];
    return op(keep, __shfl_xor_sync(0xffffffffu, send, 4));
}

__device__ __forceinline__ void gemv128(float (&d)[4], const uint32_t (&a)[8][4], uint32_t b_addr) {
    uint32_t bb[4][4];
#pragma unroll
    for (int i = 0; i < 4; i++) ldsm4(bb[i], b_addr + i * 64);
    float e[4][4];
#pragma unroll
    for (int i = 0; i < 4; i++) {
        e[i][0] = e[i][1] = e[i][2] = e[i][3] = 0.f;
        mma16816(e[i], a[2 * i], bb[i][0], bb[i][1]);
    }
#pragma unroll
    for (int i = 0; i < 4; i++) mma16816(e[i], a[2 * i + 1], bb[i][2], bb[i][3]);
#pragma unroll
    for (int k = 0; k < 4; k++) d[k] = (e[0][k] + e[1][k]) + (e[2][k] + e[3][k]);
}

__device__ __forceinline__ void fold_hilo(const float (&d)[4], int t, float& v0, float& v1) {
    const bool up = t & 2;
    float s0 = up ? d[0] : d[2], s1 = up ? d[1] : d[3];
    float k0 = up ? d[2] : d[0], k1 = up ? d[3] : d[1];
    v0 = k0 + __shfl_xor_sync(0xffffffffu, s0, 2);
    v1 = k1 + __shfl_xor_sync(0xffffffffu, s1, 2);
}

template <typename T> __device__ __forceinline__ void pin(T*& p) { asm volatile("" : "+l"(p)); }
__device__ __forceinline__ void pin(uint32_t& v) { asm volatile("" : "+r"(v)); }

struct Attn {
    uint32_t sb, xloc, xrem, xbar, wmax_st, wmax_ld, p_st, wsum, dpv;
    int wg, wp, lane;
    float acc[2][16], mref[8], ls[8], s[16];
    uint32_t pk[8];

    __device__ __forceinline__ void setup(uint32_t sb_, int rank, int wg_, int wp_, int lane_) {
        sb = sb_; wg = wg_; wp = wp_; lane = lane_;
        const int g = lane >> 2, t = lane & 3, myhead = 8 * (g >> 1) + 2 * t + (g & 1);
        xloc = sb + (wp * 32 + lane) * 16;
        xrem = map_peer(xloc, rank ^ 1);
        xbar = map_peer(sb + OFF_BAR + 8 * BAR_X, rank ^ 1);
        wmax_st = sb + OFF_WMAX + myhead * 16 + wp * 4;
        wmax_ld = sb + OFF_WMAX + t * 32;
        p_st = sb + OFF_P + wg * 4096 + (8 * (lane >> 4) + (lane & 7)) * 128 + (((2 * wp + ((lane >> 3) & 1)) ^ (lane & 7)) << 4);
        wsum = sb + OFF_WSUM + myhead * 32;
        dpv = gdesc(sb + OFF_C) + wg * 1024;
        pin(xloc); pin(xrem); pin(xbar); pin(wmax_st); pin(wmax_ld); pin(p_st); pin(wsum); pin(dpv);
#pragma unroll
        for (int i = 0; i < 16; i++) acc[0][i] = acc[1][i] = s[i] = 0.f;
#pragma unroll
        for (int i = 0; i < 8; i++) mref[i] = ls[i] = 0.f;
        reg_fence(acc[0]); reg_fence(acc[1]); reg_fence(s);
    }
    static __device__ __forceinline__ uint32_t xoff(int tile) { return tile == 2 ? OFF_X2 : OFF_X0 + (tile == 1 ? 8192u : 0u); }

    template <int TILE> __device__ __forceinline__ void scores_issue() {
        const uint32_t bar = sb + OFF_BAR + 8 * (BAR_C + TILE * 4);
        const uint32_t dc = gdesc(sb + OFF_C + TILE * 32768), dq = gdesc(sb + OFF_A);
        if (TILE == 1) nb_sync(NB_S0, 256);
        TSIF(lane == 0 && wp == 0 && TILE == 0, 52);
        const bool all = mbar_test(bar + 24) && mbar_test(bar + 16) && mbar_test(bar + 8) && mbar_test(bar);
        if (TILE >= 2) {
#pragma unroll
            for (int i = 0; i < 16; i++) s[i] = 0.f;
        }
        reg_fence(s);
        TSIF(lane == 0 && wp == 0 && TILE == 0, 53);
#pragma unroll
        for (int q = 0; q < 4; q++) {
            if (!all) mbar_spin(bar + 8 * q);
            wg_fence();
#pragma unroll
            for (int k = 0; k < 4; k++) wgmma32<0>(s, dc + q * 512 + k * 2, dq + q * 256 + k * 2);
            wg_commit();
        }
        if (TILE == 0) nb_arrive(NB_S0, 256);
        TSIF(lane == 0 && wp == 0 && TILE == 0, 54);
        wg_wait<0>();
        reg_fence(s);
        reg_fence(acc[0]);
        reg_fence(acc[1]);
#pragma unroll
        for (int i = 0; i < 4; i++) st_async4(xrem + xoff(TILE) + i * 2048, s[4 * i], s[4 * i + 1], s[4 * i + 2], s[4 * i + 3], xbar + 8 * TILE);
        TSIF(lane == 0 && wp == 0, 16 + TILE);
    }
    __device__ __forceinline__ void write_p() {
#pragma unroll
        for (int jj = 0; jj < 4; jj++) {
            pk[2 * jj] = pack_bf16(ex2(s[4 * jj]), ex2(s[4 * jj + 1]));
            pk[2 * jj + 1] = pack_bf16(ex2(s[4 * jj + 2]), ex2(s[4 * jj + 3]));
        }
        stsm4t(p_st, pk[0], pk[1], pk[2], pk[3]);
        stsm4t(p_st + 2048, pk[4], pk[5], pk[6], pk[7]);
        fence_async_smem();
    }
    __device__ __forceinline__ void exact(int st, bool mine) {
        if (mine) {
            float mx[8];
#pragma unroll
            for (int i = 0; i < 4; i++) {
                mx[2 * i] = fmaxf(s[4 * i], s[4 * i + 2]);
                mx[2 * i + 1] = fmaxf(s[4 * i + 1], s[4 * i + 3]);
            }
            stsf(wmax_st + (st & 1) * 512, reduce_heads<true>(mx, lane));
        }
        nb_sync(NB_MAIN, 256);
#pragma unroll
        for (int i = 0; i < 8; i++) {
            float d = max4(ldsf4(wmax_ld + (st & 1) * 512 + (8 * (i >> 1) + (i & 1)) * 16));
            const int r = 4 * (i >> 1) + (i & 1);
            if (st > 0) {
                d = fmaxf(d, 0.f);
                const float al = ex2(-d);
                ls[i] *= al;
                acc[0][r] *= al; acc[0][r + 2] *= al; acc[1][r] *= al; acc[1][r + 2] *= al;
            }
            mref[i] += d;
            if (mine) { s[r] -= d; s[r + 2] -= d; }
        }
        if (mine) write_p();
        reg_fence(acc[0]);
        reg_fence(acc[1]);
        nb_sync(NB_MAIN, 256);
    }
    __device__ __forceinline__ void publish_sum() { stsf(wsum + (4 * wg + wp) * 4, reduce_heads<false>(ls, lane)); }
    __device__ __forceinline__ void stage(int st) {
        const bool mine = wg == (st & 1);
        bool bad = false;
        if (mine) {
#pragma unroll
            for (int i = 0; i < 16; i++) s[i] -= mref[2 * (i >> 2) + (i & 1)];
            const uint32_t xa = xloc + xoff(st);
            mbar_spin(sb + OFF_BAR + 8 * (BAR_X + st));
#pragma unroll
            for (int i = 0; i < 4; i++) {
                const float4 r = ldsf4(xa + i * 2048);
                s[4 * i] += r.x; s[4 * i + 1] += r.y; s[4 * i + 2] += r.z; s[4 * i + 3] += r.w;
            }
            TSIF(lane == 0 && wp == 0, 20 + st);
            write_p();
            const uint32_t hi = __vimax3_u16x2(__vimax3_u16x2(pk[0], pk[1], pk[2]), __vimax3_u16x2(pk[3], pk[4], pk[5]), __vmaxu2(pk[6], pk[7]));
            const uint32_t lo = __vimin3_u16x2(__vimin3_u16x2(pk[0], pk[1], pk[2]), __vimin3_u16x2(pk[3], pk[4], pk[5]), __vminu2(pk[6], pk[7]));
            bad = max(hi >> 16, hi & 0xFFFFu) > 0x4F80u || (st == 0 && min(lo >> 16, lo & 0xFFFFu) < 0x2F80u);
        } else if (st == 3) {
            publish_sum();
        }
        const uint32_t dp = gdesc(sb + OFF_P) + (st & 1) * 256, da = dpv + st * 2048;
        wg_wait<0>();
        reg_fence(acc[0]);
        reg_fence(acc[1]);
        if (st == 2 && lane == 0) mbar_arrive(sb + OFF_BAR + 8 * BAR_CFREE);
        if (nb_sync_any(NB_MAIN, 256, bad)) {
            exact(st, mine);
            if (st == 3 && !mine) publish_sum();
        }
        wg_fence();
#pragma unroll
        for (int T = 0; T < 2; T++)
#pragma unroll
            for (int k = 0; k < 4; k++) wgmma32<1>(acc[T], da + T * 512 + k * 128, dp + k * 2);
        wg_commit();
        if (mine) {
#pragma unroll
            for (int jj = 0; jj < 4; jj++) {
                ls[2 * jj] += bf_lo(pk[2 * jj]) + bf_lo(pk[2 * jj + 1]);
                ls[2 * jj + 1] += bf_hi(pk[2 * jj]) + bf_hi(pk[2 * jj + 1]);
            }
        }
        if (st == 3) {
            if (mine) {
                publish_sum();
                if (wp == 0 && lane < 4) {
                    sts128(sb + OFF_WMAX + 1536 + lane * 32, make_uint4(__float_as_uint(mref[0]), __float_as_uint(mref[1]), __float_as_uint(mref[2]), __float_as_uint(mref[3])));
                    sts128(sb + OFF_WMAX + 1536 + lane * 32 + 16, make_uint4(__float_as_uint(mref[4]), __float_as_uint(mref[5]), __float_as_uint(mref[6]), __float_as_uint(mref[7])));
                }
            }
            nb_arrive(NB_SUM, 288);
        }
    }
    __device__ __forceinline__ void run() {
        if (wg == 0) scores_issue<0>(); else scores_issue<1>();
#pragma unroll 1
        for (int st = 0; st < 4; st++) {
            stage(st);
            if (wg == 0 && st == 0) {
                scores_issue<2>();
            } else if (wg == 1 && st == GM_S3AT) {
                scores_issue<3>();
            }
            TSIF(lane == 0 && wp == 0 && wg == 0, 24 + st);
        }
        mbar_wait(sb + OFF_BAR + 8 * BAR_GO);
        wg_wait<0>();
        reg_fence(acc[0]);
        reg_fence(acc[1]);
    }
};

__global__ void __cluster_dims__(2, 1, 1) __launch_bounds__(NTHREADS, 1)
gated_mix_kernel(const __grid_constant__ Maps maps, const __nv_bfloat16* __restrict__ x,
                 const __nv_bfloat16* __restrict__ w1, const __nv_bfloat16* __restrict__ b1,
                 const __nv_bfloat16* __restrict__ w2, const __nv_bfloat16* __restrict__ b2,
                 const __nv_bfloat16* __restrict__ gate_w, __nv_bfloat16* __restrict__ out) {
    extern __shared__ __align__(1024) unsigned char smem_raw[];
    const uint32_t sb = (smem_u32(smem_raw) + 1023u) & ~1023u;
    const uint32_t bar = sb + OFF_BAR;
    const int tid = threadIdx.x, lane = tid & 31;
    const int warp = __shfl_sync(0xffffffffu, tid >> 5, 0);
    const int cta = blockIdx.x, h = cta >> 2, j = cta & 3;
    const int rank = cta & 1, bq = cta >> 5, split = (cta >> 1) & 15;
    const int g = lane >> 2, t = lane & 3, lr = lane & 7, li = lane >> 3;
    Scratch& S = g_scratch;
    uint32_t ao[8][4];
    bool have_o = false;
    uint32_t am, ag, vb2_ld, red_st, red_ld;
    float* e5_st;
    const uint4* e5_ld;
    __nv_bfloat16* odst;
    auto tail_addresses = [&]() {
        const int b0 = 2 * (t & 1), row = g + 8 * (t >> 1);
        am = sb + OFF_MLP + (b0 * 144 + 16 * warp + row) * 4;
        ag = sb + OFF_GATE + b0 * 4;
        vb2_ld = sb + OFF_VB2 + lr * 272 + li * 16;
        red_st = sb + OFF_RED + warp * 128 + (4 * lr + ((lane & 16) ? 2 : 0) + ((lane & 8) ? 1 : 0)) * 4;
        red_ld = sb + OFF_RED + lane * 4;
        e5_st = &S.e5[2 * (9 * j + warp) + (t & 1)][h][row * 2];
        e5_ld = reinterpret_cast<const uint4*>(&S.e5[cta < 72 ? cta : 0][(4 * warp + li) & 31][lr * 4]);
        odst = out + (2 * (cta & 1) + (lane & 1)) * DM + 16 * (cta >> 1) + (lane >> 1);
        pin(am); pin(ag); pin(vb2_ld); pin(red_st); pin(red_ld); pin(e5_st); pin(e5_ld); pin(odst);
    };
    uint32_t awo = sb + OFF_C + (lr + 8 * (li >> 1)) * 304 + (2 * warp + (li & 1)) * 16;

    if (warp == 12) {
        const uint32_t t_start = now_ns();
        uint64_t pol;
        asm volatile("createpolicy.fractional.L2::evict_first.b64 %0, 1.0;" : "=l"(pol));
        const bool leader = elect_one();
        if (leader) {
            TS(0);
#pragma unroll
            for (int q = 0; q < 4; q++) {
                if (q == 0 || !GM_LEAN) {
                    if (q == 0) {
#pragma unroll
                        for (int i = 0; i < (GM_LEAN ? 1 : 4); i++) mbar_init(bar + 8 * i, 1);
                        asm volatile("fence.mbarrier_init.release.cluster;" ::: "memory");
                    }
                } else if (q == 1) {
#pragma unroll
                    for (int i = 1; i < 4; i++) mbar_init(bar + 8 * i, 1);
                    asm volatile("fence.mbarrier_init.release.cluster;" ::: "memory");
                }
                mbar_expect(bar + 8 * q, 9216);
                tma3d(sb + OFF_A + q * 9216, &maps.wq, 0, rank * 288 + q * 72, j >> 1 | h << 1, bar + 8 * q, pol);
                TSIF(q == 0, 1);
            }
        }
        __syncwarp();
        nb_sync(NB_INIT, NTHREADS);
        cluster_arrive();
        if (leader) {
            auto pace = [&](int i) {
                const uint32_t due = GM_T0 + i * GM_DT - max(i - GM_K2, 0) * (GM_DT - GM_DT2) - max(i - BAR_WUV, 0) * (GM_DT2 - GM_DT3);
                if (i >= GM_W) mbar_spin(bar + 8 * (i - GM_W));
                int it = 0;
                while (now_ns() - t_start < due && ++it < SPIN_LIMIT) {}
            };
#pragma unroll 1
            for (int q = 0; q < 4; q++) {
                const int i = BAR_WUK + q;
                pace(i);
                mbar_expect(bar + 8 * i, 8192);
                tma3d(sb + OFF_B + q * 8192, &maps.wuk, 0, rank * 256 + q * 64, j >> 1 | h << 1, bar + 8 * i, pol);
            }
#pragma unroll 1
            for (int q = 0; q < 16; q++) {
                const int i = BAR_C + q;
                pace(i);
                mbar_expect(bar + 8 * i, 8192);
                tma3d(sb + OFF_C + q * 8192, &maps.ckv, 0, (cta >> 1) * 256 + (q >> 2) * 64, 4 * rank + (q & 3), bar + 8 * i, pol);
            }
            mbar_spin(bar + 8 * BAR_BFREE);
#pragma unroll 1
            for (int q = 0; q < 4; q++) {
                const int i = BAR_WUV + q;
                pace(i);
                mbar_expect(bar + 8 * i, 8192);
                tma3d(sb + OFF_B + (q & 1) * 16384 + (q >> 1) * 8192, &maps.wuv, 0, j * 128 + (q >> 1) * 64, 2 * h + (q & 1), bar + 8 * i, pol);
            }
            mbar_spin(bar + 8 * BAR_CFREE);
#pragma unroll 1
            for (int q = 0; q < 4 - GM_HOLD; q++) {
                const int i = BAR_WO + q;
                pace(i);
                mbar_expect(bar + 8 * i, 9728);
                tma3d(sb + OFF_C + q * 9728, &maps.wo, j * 144, h * 128 + q * 32, 0, bar + 8 * i, pol);
            }
#pragma unroll
            for (int q = 4 - GM_HOLD; q < 4; q++) mbar_expect(bar + 8 * (BAR_WO + q), 9728);
            mbar_spin(bar + 8 * BAR_PREAD);
            if (GM_HDEL) spin_clk(GM_HDEL);
#pragma unroll
            for (int q = 4 - GM_HOLD; q < 4; q++) tma3d(sb + OFF_C + q * 9728, &maps.wo, j * 144, h * 128 + q * 32, 0, bar + 8 * (BAR_WO + q), pol);
        }
        TS_END();
        return;
    }
    if (warp >= 13) {
        const bool leader = elect_one();
        if (leader && warp == 13) {
            mbar_init(bar + 8 * BAR_IN, 1);
            asm volatile("fence.mbarrier_init.release.cluster;" ::: "memory");
            mbar_expect(bar + 8 * BAR_IN, 4608 + 1152 + 864);
            bulk_load(sb + OFF_X, x, 4608, bar + 8 * BAR_IN);
            bulk_load(sb + OFF_GW, gate_w, 1152, bar + 8 * BAR_IN);
            bulk_load(sb + OFF_W1, w1 + h * 144, 288, bar + 8 * BAR_IN);
            bulk_load(sb + OFF_W1 + 288, b1 + h * 144, 288, bar + 8 * BAR_IN);
            bulk_load(sb + OFF_W1 + 576, w2 + h * 144, 288, bar + 8 * BAR_IN);
            mbar_init(bar + 8 * BAR_XQ, 1);
            mbar_init(bar + 8 * BAR_QW, 8);
            mbar_init(bar + 8 * BAR_PVDONE, 8);
            mbar_init(bar + 8 * BAR_PREAD, 1);
            asm volatile("fence.mbarrier_init.release.cluster;" ::: "memory");
            mbar_expect(bar + 8 * BAR_XQ, 2048);
        }
        __syncwarp();
        if (warp == 13) {
#pragma unroll
            for (int i = 0; i < 4; i++) st_zero4(&S.qabs[j >> 1][i][4 * rank + li][h][lr * 4]);
        }
        nb_sync(NB_INIT, NTHREADS);
        cluster_arrive();
        auto arrive = [&](unsigned* ctr, int ts) {
            unsigned old = 0;
            __syncwarp();
            if (leader) {
                asm volatile("atom.add.release.gpu.global.u32 %0, [%1], 1;" : "=r"(old) : "l"(ctr) : "memory");
                TS(ts);
            }
            __syncwarp();
            return (old & ~(unsigned)(NCTA - 1)) + NCTA;
        };
        auto wait_all = [&](const unsigned* ctr, unsigned target, int go, int ts) {
            if (leader) {
                int it = 0;
                while (true) {
                    unsigned v;
                    asm volatile("ld.acquire.gpu.global.u32 %0, [%1];" : "=r"(v) : "l"(ctr) : "memory");
                    if ((int)(v - target) >= 0) break;
                    if (++it > SPIN_LIMIT) __trap();
                    __nanosleep(GM_QSLEEP);
                }
                mbar_arrive(bar + 8 * go);
                TS(ts);
            }
            __syncwarp();
        };
        auto clear_late = [&]() {
            char* pp = reinterpret_cast<char*>(&S.part[0][2 * rank + li / 2][bq][split][(lane & 15) * 4]);
#pragma unroll 1
            for (int i = 0; i < 32; i++) {
                st_zero4(pp + i * sizeof(S.part[0]));
                spin_clk(GM_CLRGAP);
            }
#pragma unroll
            for (int i = 0; i < 4; i++) st_zero4(&S.e4[h][j][i][lane * 4]);
#pragma unroll
            for (int i = 0; i < 5; i++)
                if (4 * i + li < 18) st_zero4(&S.e5[18 * j + 4 * i + li][h][lr * 4]);
            if (lane < 8) st_zero4(reinterpret_cast<uint4*>(&S.ml[0][0][0]) + cta * 8 + lane);
            TSIF(lane == 0, 10);
        };
        if (warp == 13) {
            wait_all(&g_count[0][0], arrive(&g_count[0][0], 9), BAR_QGATE, 11);
            TS_END();
            return;
        }
        if (GM_CLRAT >= 0) mbar_wait(bar + 8 * GM_CLRAT);
        clear_late();
        wait_all(&g_count[1][0], arrive(&g_count[1][0], 4), BAR_GO, 5);
        {
            float2* dst = &S.ml[lane][bq][split];
            pin(dst);
            mbar_wait(bar + 8 * BAR_GO);
            nb_sync(NB_SUM, 288);
            const float l = sum4(ldsf4(sb + OFF_WSUM + lane * 32)) + sum4(ldsf4(sb + OFF_WSUM + lane * 32 + 16));
            const float m = ldsf(sb + OFF_WMAX + 1536 + ((lane >> 1) & 3) * 32 + (2 * (lane >> 3) + (lane & 1)) * 4);
            if (rank == 0) st_rlx2(dst, nzf(m), nzf(l));
        }
        TS_END();
        return;
    }

    if (warp >= 8) {
        const int b = warp - 8, mt = tid - 256;
        uint32_t xv[9], gv[9];
        float hv[9], acc[9];
        const float bias2 = (h == 0 && lane < 16) ? __bfloat162float(b2[0]) : 0.f;
        nb_sync(NB_INIT, NTHREADS);
        cluster_arrive();
        mbar_wait(bar + 8 * BAR_IN);
#pragma unroll
        for (int k = 0; k < 9; k++) {
            xv[k] = lds32(sb + OFF_X + b * (DM * 2) + (lane + 32 * k) * 4);
            gv[k] = lds32(sb + OFF_GW + (lane + 32 * k) * 4);
            hv[k] = lds_bf16(sb + OFF_X + (b * DM + j * 144 + (lane & 15) + 16 * k) * 2);
        }
#pragma unroll
        for (int i = 0; i < 2; i++) {
            const int f = mt + 128 * i;
            if (f < 144) {
                const float cw = lds_bf16(sb + OFF_W1 + f * 2), cb = lds_bf16(sb + OFF_W1 + 288 + f * 2), cv = lds_bf16(sb + OFF_W1 + 576 + f * 2);
                sts128(sb + OFF_COEF + f * 16, make_uint4(__float_as_uint(cw), __float_as_uint(cb), __float_as_uint(0.5f * cv), 0u));
            }
        }
        float sum = 0.f, z = 0.f;
#pragma unroll
        for (int k = 0; k < 9; k++) {
            sum += bf_lo(xv[k]) + bf_hi(xv[k]);
            z = fmaf(bf_lo(xv[k]), bf_lo(gv[k]), fmaf(bf_hi(xv[k]), bf_hi(gv[k]), z));
        }
#pragma unroll
        for (int o = 16; o; o >>= 1) {
            sum += __shfl_xor_sync(0xffffffffu, sum, o);
            z += __shfl_xor_sync(0xffffffffu, z, o);
        }
        const float mean = sum * (1.f / DM);
        float var = 0.f;
#pragma unroll
        for (int k = 0; k < 9; k++) {
            const float d0 = bf_lo(xv[k]) - mean, d1 = bf_hi(xv[k]) - mean;
            var = fmaf(d0, d0, fmaf(d1, d1, var));
        }
#pragma unroll
        for (int o = 16; o; o >>= 1) var += __shfl_xor_sync(0xffffffffu, var, o);
        const float rstd = rsqrtf(var * (1.f / DM) + 1e-5f);
        const float gate = __fdividef(1.f, 1.f + __expf(-z));
        if (lane == 0) stsf(sb + OFF_GATE + b * 4, gate);
#pragma unroll
        for (int k = 0; k < 9; k++) { hv[k] = (hv[k] - mean) * rstd; acc[k] = 0.f; }
        nb_arrive(NB_Q, 384);
        nb_sync(NB_MLP, 128);
        TSIF(mt == 0, 3);
        float p0 = 0.f, p1 = bias2;
        const uint32_t ca = sb + OFF_COEF + (lane >> 4) * 72 * 16;
        constexpr float K0 = 0.7978845608028654f, K1 = 0.7978845608028654f * 0.044715f;
        float u[9], u2[9], tt[9], in[9], hu[9], th[9];
        float4 c = ldsf4(ca), cn = ldsf4(ca + 16);
#pragma unroll
        for (int q = 0; q < 9; q++) th[q] = hu[q] = 0.f;
#pragma unroll
        for (int q = 0; q < 4; q++) { u[q] = fmaf(hv[q], c.x, c.y); u2[q] = u[q] * u[q]; tt[q] = fmaf(u2[q], K1, K0); }
        in[0] = u[0] * tt[0];
        hu[0] = u[0] * c.z;
        int f = 0;
#pragma unroll 1
        for (int seg = 0; seg < 3; seg++) {
            const int fend = seg == 0 ? GM_MLP1 : seg == 1 ? GM_MLP2 : GM_MLPN;
            if (seg > 0) {
                TSIF(mt == 0, 46 + 2 * seg);
                mbar_wait(bar + 8 * (seg == 1 ? BAR_QW : BAR_PVDONE));
                TSIF(mt == 0, 47 + 2 * seg);
            }
#pragma unroll 2
            for (; f < fend; f++) {
                const float4 cnn = ldsf4(ca + (f + 2) * 16);
                p0 = fmaf(c.x, c.z, p0);
                p1 = fmaf(c.y, c.z, p1);
#pragma unroll
                for (int q = 0; q < 9; q++) {
                    const int q1 = (q + 1) % 9, q2 = (q + 2) % 9, q3 = (q + 3) % 9, q4 = (q + 4) % 9, qm = (q + 6) % 9;
                    asm volatile("fma.rn.f32 %0, %1, %2, %0;" : "+f"(acc[qm]) : "f"(hu[qm]), "f"(th[qm]));
                    asm volatile("tanh.approx.f32 %0, %1;" : "=f"(th[q]) : "f"(in[q]));
                    asm volatile("fma.rn.f32 %0, %1, %2, %3;" : "=f"(u[q4]) : "f"(hv[q4]), "f"(q + 4 >= 9 ? cn.x : c.x), "f"(q + 4 >= 9 ? cn.y : c.y));
                    asm volatile("mul.rn.f32 %0, %1, %1;" : "=f"(u2[q3]) : "f"(u[q3]));
                    asm volatile("fma.rn.f32 %0, %1, %2, %3;" : "=f"(tt[q2]) : "f"(u2[q2]), "f"(K1), "f"(K0));
                    asm volatile("mul.rn.f32 %0, %1, %2;" : "=f"(in[q1]) : "f"(u[q1]), "f"(tt[q1]));
                    asm volatile("mul.rn.f32 %0, %1, %2;" : "=f"(hu[q1]) : "f"(u[q1]), "f"(q + 1 >= 9 ? cn.z : c.z));
                }
                c = cn;
                cn = cnn;
            }
        }
#pragma unroll
        for (int q = 6; q < 9; q++) acc[q] = fmaf(hu[q], th[q], acc[q]);
        const float og = 1.f - gate;
#pragma unroll
        for (int k = 0; k < 9; k++) {
            float v = acc[k] + fmaf(hv[k], p0, p1);
            v += __shfl_xor_sync(0xffffffffu, v, 16);
            if (lane < 16) stsf(sb + OFF_MLP + (b * 144 + lane + 16 * k) * 4, og * v);
        }
        TSIF(mt == 0, 8);
        if (warp >= 9) {
            nb_arrive(NB_O, 384);
            TS_END();
            return;
        }
        tail_addresses();
    } else {
        const int wg = warp >> 2, wp = warp & 3;
        if (elect_one()) {
#pragma unroll
            for (int i = 0; i < 4; i++) mbar_init(bar + 8 * (4 + 4 * warp + i), 1);
            if (warp == 7) {
#pragma unroll
                for (int i = 0; i < 4; i++) mbar_expect(bar + 8 * (BAR_X + i), 8192);
            }
            if (warp < 4) mbar_init(bar + 8 * (BAR_BFREE + warp), warp < 2 ? 8 : 1);
            asm volatile("fence.mbarrier_init.release.cluster;" ::: "memory");
        }
        __syncwarp();
        nb_sync(NB_INIT, NTHREADS);
        cluster_arrive();

        {
            uint32_t xb[9][2];
            mbar_wait(bar + 8 * BAR_IN);
#pragma unroll
            for (int ks = 0; ks < 9; ks++) {
                const uint32_t px = sb + OFF_X + ((g & 3) * DM + rank * 288 + wg * 144 + ks * 16) * 2 + t * 4;
                xb[ks][0] = g < 4 ? lds32(px) : 0u;
                xb[ks][1] = g < 4 ? lds32(px + 16) : 0u;
            }
            float d[4] = {0.f, 0.f, 0.f, 0.f};
            const uint32_t a0 = sb + OFF_A + (wg * 144 + lr + 8 * (li >> 1)) * 128 + (((2 * wp + (li & 1)) ^ lr) << 4);
            const uint32_t ql = sb + OFF_P + (2 * rank + wg) * 1024 + (16 * wp + g) * 16 + (t & 1) * 8;
            const uint32_t qr = map_peer(ql, rank ^ 1), qb = map_peer(bar + 8 * BAR_XQ, rank ^ 1);
            cluster_wait();
            mbar_wait(bar + 8 * (BAR_WQ + 2 * wg));
            mbar_wait(bar + 8 * (BAR_WQ + 2 * wg + 1));
#pragma unroll
            for (int ks = 0; ks < 9; ks++) {
                uint32_t a[4];
                ldsm4t(a, a0 + ks * 2048);
                mma16816(d, a, xb[ks][0], xb[ks][1]);
            }
            if (t < 2) {
                st_async2(qr, d[0], d[1], qb);
                st_async2(qr + 128, d[2], d[3], qb);
                asm volatile("st.shared.v2.f32 [%0], {%1,%2};" ::"r"(ql), "f"(d[0]), "f"(d[1]) : "memory");
                asm volatile("st.shared.v2.f32 [%0], {%1,%2};" ::"r"(ql + 128), "f"(d[2]), "f"(d[3]) : "memory");
            }
            nb_sync(NB_MAIN, 256);
            TSIF(tid == 0, 12);
            if (tid < 128) {
                mbar_wait(bar + 8 * BAR_XQ);
                const uint32_t qa = sb + OFF_P + tid * 8;
                const float2 v0 = ldsf2(qa), v1 = ldsf2(qa + 1024), v2 = ldsf2(qa + 2048), v3 = ldsf2(qa + 3072);
                const float q0 = (v0.x + v1.x) + (v2.x + v3.x), q1 = (v0.y + v1.y) + (v2.y + v3.y);
                const uint32_t hi = pack_bf16(q0, q1);
                const uint32_t lo = pack_bf16(q0 - bf_lo(hi), q1 - bf_hi(hi));
                const uint32_t a = sb + OFF_VB + (2 * (tid & 1)) * 272 + (tid >> 1) * 2;
                sts16(a, hi & 0xFFFFu);
                sts16(a + 272, hi >> 16);
                sts16(a + 4 * 272, lo & 0xFFFFu);
                sts16(a + 5 * 272, lo >> 16);
            }
        }
        TSIF(tid == 0, 13);
        {
            uint32_t a[2][4][4];
            const uint32_t a0 = sb + OFF_B + (32 * warp + lr + 8 * (li & 1)) * 128;
            const bool odd = g & 1;
            const int cl = 32 * warp + (g & ~1) + 8 * (t >> 1);
            uint32_t* dst = &S.qabs[j >> 1][2 * (t & 1) + (odd ? 1 : 0)][4 * rank + (cl >> 6)][h][(cl & 7) >> 1];
            const int ch = (cl & 63) >> 3;
            mbar_wait(bar + 8 * (BAR_WUK + (warp >> 1)));
#pragma unroll
            for (int mt = 0; mt < 2; mt++)
#pragma unroll
                for (int ks = 0; ks < 4; ks++) ldsm4(a[mt][ks], a0 + mt * 2048 + (((2 * ks + (li >> 1)) ^ lr) << 4));
            nb_sync(NB_Q, 384);
            uint32_t bb[2][4];
            ldsm4(bb[0], sb + OFF_VB + lr * 272 + li * 16);
            ldsm4(bb[1], sb + OFF_VB + lr * 272 + li * 16 + 64);
            if (lane == 0) mbar_arrive(bar + 8 * BAR_BFREE);
#pragma unroll
            for (int mt = 0; mt < 2; mt++) {
                float d[4] = {0.f, 0.f, 0.f, 0.f};
#pragma unroll
                for (int ks = 0; ks < 4; ks++) mma16816(d, a[mt][ks], bb[ks >> 1][2 * (ks & 1)], bb[ks >> 1][2 * (ks & 1) + 1]);
                float v0, v1;
                fold_hilo(d, t, v0, v1);
                const float sc = 0.08838834764831845f * 1.4426950408889634f;
                v0 *= sc; v1 *= sc;
                const float got = __shfl_xor_sync(0xffffffffu, odd ? v0 : v1, 4);
                const uint32_t w = odd ? pack_bf16(got, v1) : pack_bf16(v0, got);
                st_rlx(dst + (((ch + 2 * mt) ^ (h & 7)) << 2), nz(w));
            }
            __syncwarp();
            if (lane == 0) mbar_arrive(bar + 8 * BAR_QW);
        }
        TSIF(tid == 0, 14);
        uint32_t* part_st = &S.part[2 * t][2 * rank + wg][bq][split][wp * 16 + g * 2];
        const uint4* part_ld = reinterpret_cast<const uint4*>(&S.part[h][j][warp >> 1][li][(warp & 1) * 32 + lr * 4]);
        const float2* ml_ld = &S.ml[h][warp >> 1][lane & 15];
        pin(part_st); pin(part_ld); pin(ml_ld);

        Attn at;
        {
            const uint4* src = reinterpret_cast<const uint4*>(&S.qabs[0][bq][4 * rank][0][0]) + tid;
            constexpr int HALF = sizeof(S.qabs[0]) / 16;
            pin(src);
            at.setup(sb, rank, wg, wp, lane);
            mbar_spin(bar + 8 * BAR_QGATE);
            spin_clk(GM_E2DELAY);
            TSIF(tid == 0, 2);
            uint4 v[8];
#pragma unroll
            for (int i = 0; i < 8; i++) {
                v[i] = (GM_HINT & 1) ? ld_rlx4_ef(src + (i >> 2) * HALF + (i & 3) * 256) : ld_rlx4(src + (i >> 2) * HALF + (i & 3) * 256);
                if (GM_E2GAP && (i & 1) && i < 7) spin_clk(GM_E2GAP);
            }
            tensor_warmup();
            int it = 0;
            while (true) {
                uint32_t mn[8];
#pragma unroll
                for (int i = 0; i < 8; i++) mn[i] = min4(v[i]);
                if (min(__vimin3_u32(__vimin3_u32(mn[0], mn[1], mn[2]), __vimin3_u32(mn[3], mn[4], mn[5]), mn[6]), mn[7]) != 0u) break;
#pragma unroll
                for (int i = 0; i < 8; i++)
                    if (mn[i] == 0u) v[i] = ld_rlx4(src + (i >> 2) * HALF + (i & 3) * 256);
                if (++it > SPIN_LIMIT) __trap();
            }
            TSIF(tid == 0, 55);
            auto add2 = [](uint32_t x, uint32_t y) { uint32_t r; asm("add.rn.bf16x2 %0, %1, %2;" : "=r"(r) : "r"(x), "r"(y)); return r; };
#pragma unroll
            for (int i = 0; i < 4; i++)
                asm volatile("st.shared.v4.u32 [%0], {%1,%2,%3,%4};" ::"r"(sb + OFF_A + (tid + 256 * i) * 16),
                             "r"(add2(v[i].x, v[i + 4].x)), "r"(add2(v[i].y, v[i + 4].y)), "r"(add2(v[i].z, v[i + 4].z)), "r"(add2(v[i].w, v[i + 4].w)) : "memory");
            fence_async_smem();
            nb_sync(NB_MAIN, 256);
        }
        TSIF(tid == 0, 15);

        at.run();

        TSIF(tid == 0, 27);
#pragma unroll
        for (int i = 0; i < 8; i++) {
            const int r = 4 * (i >> 1) + (i & 1);
            if (GM_HINT & 4) st_rlx2_ef(part_st + (8 * (i >> 1) + (i & 1)) * (4 * 4 * 16 * 64),
                    nz(pack_bf16(at.acc[0][r], at.acc[0][r + 2])), nz(pack_bf16(at.acc[1][r], at.acc[1][r + 2])));
            else st_rlx2(part_st + (8 * (i >> 1) + (i & 1)) * (4 * 4 * 16 * 64),
                    nz(pack_bf16(at.acc[0][r], at.acc[0][r + 2])), nz(pack_bf16(at.acc[1][r], at.acc[1][r + 2])));
        }
        TSIF(tid == 0, 28);
        if (lane == 0) mbar_arrive(bar + 8 * BAR_PVDONE);

        uint32_t a[8][4];
        tail_addresses();
        float* e4_st = &S.e4[h][j][2 * (t & 1)][16 * warp + g + 8 * (t >> 1)];
        const float* e4_ld = &S.e4[h][0][tid >> 6][2 * (tid & 63)];
        uint32_t vb_ld = sb + OFF_VB + lr * 272 + li * 16, vb2_st = sb + OFF_VB2 + (tid >> 6) * 272 + (tid & 63) * 4;
        uint32_t auv = sb + OFF_B + wg * 16384 + (lr + 8 * (li >> 1)) * 128 + (((2 * wp + (li & 1)) ^ lr) << 4);
        const bool u16 = lane & 16, u8 = lane & 8;
        uint32_t vb_st = sb + OFF_VB + (warp >> 1) * 272 + ((u16 ? 64 : 0) + 16 * (2 * (warp & 1) + (lr >> 2)) + (u8 ? 8 : 0) + 2 * (lr & 3)) * 2;
        uint32_t first = tid == 0, bar_pread = bar + 8 * BAR_PREAD;
        pin(e4_st); pin(e4_ld); pin(vb_ld); pin(vb2_st); pin(auv); pin(vb_st); pin(awo); pin(first); pin(bar_pread);
        auto load_wo_early = [&]() {
#pragma unroll
            for (int ks = 0; ks < 8 - 2 * GM_HOLD; ks++) {
                if ((ks & 1) == 0) mbar_spin(bar + 8 * (BAR_WO + (ks >> 1)));
                ldsm4t(ao[ks], awo + ks * 16 * 304);
            }
        };
        {
            uint2 mlv = ld_rlx2(ml_ld);
            uint4 v[4];
            if (!GM_E3GATE) {
#pragma unroll
                for (int i = 0; i < 4; i++) v[i] = ld_rlx4(part_ld + i * 64);
            }
            int it = 0;
            while (!__all_sync(0xffffffffu, full2(mlv))) {
                mlv = ld_rlx2(ml_ld);
                if (++it > SPIN_LIMIT) __trap();
            }
            if (GM_E3GATE) {
#pragma unroll
                for (int i = 0; i < 4; i++) v[i] = ld_rlx4(part_ld + i * 64);
            }
            mbar_arrive_if(bar_pread, first);
            const float m = __uint_as_float(mlv.x);
            float M = m;
#pragma unroll
            for (int o = 8; o; o >>= 1) M = fmaxf(M, __shfl_xor_sync(0xffffffffu, M, o));
            const float e = ex2(m - M);
            float L = e * __uint_as_float(mlv.y);
#pragma unroll
            for (int o = 8; o; o >>= 1) L += __shfl_xor_sync(0xffffffffu, L, o);
            const float wgt = __fdividef(e, L);
            float w[4];
#pragma unroll
            for (int i = 0; i < 4; i++) w[i] = __shfl_sync(0xffffffffu, wgt, 4 * i + li);
            TSIF(tid == 0, 29);
            bool have = false;
            it = 0;
            while (true) {
                if (!have && mbar_test(bar + 8 * (BAR_WUV + wg)) && mbar_test(bar + 8 * (BAR_WUV + 2 + wg))) {
                    have = true;
#pragma unroll
                    for (int ks = 0; ks < 8; ks++) ldsm4t(a[ks], auv + ks * 2048);
                }
                const uint32_t m0 = min4(v[0]), m1 = min4(v[1]), m2 = min4(v[2]), m3 = min4(v[3]);
                if (__all_sync(0xffffffffu, min(__vimin3_u32(m0, m1, m2), m3) != 0u)) break;
                if (m0 == 0u) v[0] = ld_rlx4(part_ld);
                if (m1 == 0u) v[1] = ld_rlx4(part_ld + 64);
                if (m2 == 0u) v[2] = ld_rlx4(part_ld + 128);
                if (m3 == 0u) v[3] = ld_rlx4(part_ld + 192);
                if (++it > SPIN_LIMIT) __trap();
            }
            TSIF(tid == 0, 30);
            float c[8];
#pragma unroll
            for (int i = 0; i < 8; i++) c[i] = 0.f;
#pragma unroll
            for (int i = 0; i < 4; i++) {
                c[0] = fmaf(w[i], bf_lo(v[i].x), c[0]); c[1] = fmaf(w[i], bf_hi(v[i].x), c[1]);
                c[2] = fmaf(w[i], bf_lo(v[i].y), c[2]); c[3] = fmaf(w[i], bf_hi(v[i].y), c[3]);
                c[4] = fmaf(w[i], bf_lo(v[i].z), c[4]); c[5] = fmaf(w[i], bf_hi(v[i].z), c[5]);
                c[6] = fmaf(w[i], bf_lo(v[i].w), c[6]); c[7] = fmaf(w[i], bf_hi(v[i].w), c[7]);
            }
            float r0 = (u16 ? c[2] : c[0]) + __shfl_xor_sync(0xffffffffu, u16 ? c[0] : c[2], 16);
            float r1 = (u16 ? c[3] : c[1]) + __shfl_xor_sync(0xffffffffu, u16 ? c[1] : c[3], 16);
            float r2 = (u16 ? c[6] : c[4]) + __shfl_xor_sync(0xffffffffu, u16 ? c[4] : c[6], 16);
            float r3 = (u16 ? c[7] : c[5]) + __shfl_xor_sync(0xffffffffu, u16 ? c[5] : c[7], 16);
            const float y0 = (u8 ? r1 : r0) + __shfl_xor_sync(0xffffffffu, u8 ? r0 : r1, 8);
            const float y1 = (u8 ? r3 : r2) + __shfl_xor_sync(0xffffffffu, u8 ? r2 : r3, 8);
            const uint32_t hi = pack_bf16(y0, y1);
            const uint32_t lo = pack_bf16(y0 - bf_lo(hi), y1 - bf_hi(hi));
            sts32(vb_st, hi);
            sts32(vb_st + 4 * 272, lo);
            if (!have) {
                mbar_wait(bar + 8 * (BAR_WUV + wg));
                mbar_wait(bar + 8 * (BAR_WUV + 2 + wg));
#pragma unroll
                for (int ks = 0; ks < 8; ks++) ldsm4t(a[ks], auv + ks * 2048);
            }
        }
        {
            nb_sync(NB_MAIN, 256);
            TSIF(tid == 0, 31);
            float d0[4];
            gemv128(d0, a, vb_ld);
            float v0, v1;
            fold_hilo(d0, t, v0, v1);
            st_rlx(e4_st, nzf(v0));
            st_rlx(e4_st + 128, nzf(v1));
            load_wo_early();
        }
        TSIF(tid == 0, 32);
        {
            const float* src = e4_ld;
            uint2 v[4];
            spin_clk(GM_E4DELAY);
#pragma unroll
            for (int i = 0; i < 4; i++) v[i] = ld_rlx2(src + i * 512);
            bool have = false;
            int it = 0;
            while (true) {
                if (!have && mbar_test(bar + 8 * (BAR_WO + 3)) && mbar_test(bar + 8 * (BAR_WO + 2)) &&
                    (GM_HOLD < 3 || mbar_test(bar + 8 * (BAR_WO + 1)))) {
                    have = true;
#pragma unroll
                    for (int ks = 8 - 2 * GM_HOLD; ks < 8; ks++) ldsm4t(ao[ks], awo + ks * 16 * 304);
                }
                if (__all_sync(0xffffffffu, min(__vimin3_u32(min2(v[0]), min2(v[1]), min2(v[2])), min2(v[3])) != 0u)) break;
#pragma unroll
                for (int i = 0; i < 4; i++) v[i] = ld_rlx2(src + i * 512);
                if (++it > SPIN_LIMIT) __trap();
            }
            const float y0 = (__uint_as_float(v[0].x) + __uint_as_float(v[1].x)) + (__uint_as_float(v[2].x) + __uint_as_float(v[3].x));
            const float y1 = (__uint_as_float(v[0].y) + __uint_as_float(v[1].y)) + (__uint_as_float(v[2].y) + __uint_as_float(v[3].y));
            const uint32_t hi = pack_bf16(y0, y1);
            const uint32_t lo = pack_bf16(y0 - bf_lo(hi), y1 - bf_hi(hi));
            sts32(vb2_st, hi);
            sts32(vb2_st + 4 * 272, lo);
            have_o = have;
        }
        TSIF(tid == 0, 33);
    }

    {
        if (!have_o) {
#pragma unroll
            for (int ks = 0; ks < 8; ks++) {
                if (ks < 8 - 2 * GM_HOLD && warp < 8) continue;
                if ((ks & 1) == 0) mbar_spin(bar + 8 * (BAR_WO + (ks >> 1)));
                ldsm4t(ao[ks], awo + ks * 16 * 304);
            }
        }
        const bool u16 = lane & 16, u8 = lane & 8;
        nb_sync(NB_O, 384);
        TSIF(tid == 0, 34);
        float d0[4];
        gemv128(d0, ao, vb2_ld);
        const float g0 = ldsf(ag), g1 = ldsf(ag + 4);
        const float m0 = ldsf(am), m1 = ldsf(am + 144 * 4);
        float v0, v1;
        fold_hilo(d0, t, v0, v1);
        st_rlx2(e5_st, nzf(fmaf(g0, v0, m0)), nzf(fmaf(g1, v1, m1)));
        TSIF(tid == 0, 35);
        if (cta < 72 && warp < 8) {
            spin_clk(GM_E5DELAY);
            uint4 v;
            int it = 0;
            do {
                v = ld_rlx4(e5_ld);
                if (++it > SPIN_LIMIT) __trap();
            } while (!__all_sync(0xffffffffu, full4(v)));
            const float c0 = __uint_as_float(v.x), c1 = __uint_as_float(v.y), c2 = __uint_as_float(v.z), c3 = __uint_as_float(v.w);
            const float r0 = (u16 ? c2 : c0) + __shfl_xor_sync(0xffffffffu, u16 ? c0 : c2, 16);
            const float r1 = (u16 ? c3 : c1) + __shfl_xor_sync(0xffffffffu, u16 ? c1 : c3, 16);
            stsf(red_st, (u8 ? r1 : r0) + __shfl_xor_sync(0xffffffffu, u8 ? r0 : r1, 8));
            if (warp == 0) {
                nb_sync(NB_MAIN, 256);
                TSIF(lane == 0, 36);
                float y[8];
#pragma unroll
                for (int i = 0; i < 8; i++) y[i] = ldsf(red_ld + i * 128);
                *odst = __float2bfloat16(((y[0] + y[1]) + (y[2] + y[3])) + ((y[4] + y[5]) + (y[6] + y[7])));
                TSIF(lane == 0, 37);
            } else {
                nb_arrive(NB_MAIN, 256);
            }
        }
    }
    TS_END();
}

typedef CUresult (*EncodeTiledFn)(CUtensorMap*, CUtensorMapDataType, cuuint32_t, void*, const cuuint64_t*, const cuuint64_t*,
                                  const cuuint32_t*, const cuuint32_t*, CUtensorMapInterleave, CUtensorMapSwizzle,
                                  CUtensorMapL2promotion, CUtensorMapFloatOOBfill);

static void encode_map(EncodeTiledFn enc, CUtensorMap* m, const void* p, uint64_t rows, uint64_t cols, uint64_t group_cols,
                       uint32_t box_cols, uint32_t box_rows, CUtensorMapSwizzle swz) {
    cuuint64_t dims[3] = {group_cols, rows, cols / group_cols};
    cuuint64_t strides[2] = {cols * 2, group_cols * 2};
    cuuint32_t box[3] = {box_cols, box_rows, 1};
    cuuint32_t es[3] = {1, 1, 1};
    enc(m, CU_TENSOR_MAP_DATA_TYPE_BFLOAT16, 3, const_cast<void*>(p), dims, strides, box, es, CU_TENSOR_MAP_INTERLEAVE_NONE,
        swz, GM_PROMO, CU_TENSOR_MAP_FLOAT_OOB_FILL_NONE);
}

}

extern "C" void kernel_launch(void* const* d_in, const int* in_sizes, int n_in, void* d_out, int out_size) {
    using namespace gm;
    (void)in_sizes; (void)n_in; (void)out_size;
    static EncodeTiledFn enc = nullptr;
    if (!enc) {
        void* fn = nullptr;
        cudaDriverEntryPointQueryResult q;
        cudaGetDriverEntryPoint("cuTensorMapEncodeTiled", &fn, cudaEnableDefault, &q);
        enc = (EncodeTiledFn)fn;
        cudaFuncSetAttribute(gated_mix_kernel, cudaFuncAttributeMaxDynamicSharedMemorySize, SMEM_BYTES);
    }
    Maps maps;
    encode_map(enc, &maps.wq, d_in[2], 576, 4096, 64, 64, 72, CU_TENSOR_MAP_SWIZZLE_128B);
    encode_map(enc, &maps.wuk, d_in[3], 512, 4096, 64, 64, 64, CU_TENSOR_MAP_SWIZZLE_128B);
    encode_map(enc, &maps.ckv, d_in[1], 16384, 512, 64, 64, 64, CU_TENSOR_MAP_SWIZZLE_128B);
    encode_map(enc, &maps.wuv, d_in[4], 512, 4096, 64, 64, 64, CU_TENSOR_MAP_SWIZZLE_128B);
    encode_map(enc, &maps.wo, d_in[5], 4096, 576, 576, 152, 32, CU_TENSOR_MAP_SWIZZLE_NONE);
    gated_mix_kernel<<<NCTA, NTHREADS, SMEM_BYTES>>>(
        maps, (const __nv_bfloat16*)d_in[0], (const __nv_bfloat16*)d_in[7], (const __nv_bfloat16*)d_in[8],
        (const __nv_bfloat16*)d_in[9], (const __nv_bfloat16*)d_in[10], (const __nv_bfloat16*)d_in[11],
        (__nv_bfloat16*)d_out);
}
```
